```python
import torch

def _softmax(x, axis=-1):
    return torch.softmax(x, dim=axis)
def _gelu(x):
    return torch.nn.functional.gelu(x, approximate="tanh")
def _silu(x):
    return torch.nn.functional.silu(x)
def _sigmoid(x):
    return torch.sigmoid(x)
def _layernorm(x, axis=-1, eps=1e-5):
    m = x.mean(dim=axis, keepdim=True)
    v = x.var(dim=axis, keepdim=True, unbiased=False)
    return (x - m) / torch.sqrt(v + eps)
def _scatter_add(tgt, idx, src, axis=0):
    return tgt.clone().index_add_(axis, idx, src)
def _segment_sum(src, seg, n):
    out = torch.zeros((n,) + src.shape[1:], dtype=src.dtype)
    return out.index_add_(0, seg, src)
def _pad(x, pw):
    flat = tuple(v for pair in reversed(pw) for v in pair)
    return torch.nn.functional.pad(x, flat)

kernel_name = 'parallel_sum__ssm_conv_h3__dense_activation_gelu__prompt'

def setup_inputs():

    _w = (lambda a: (lambda t: t.to(torch.bfloat16) if t.is_floating_point() else t)(torch.as_tensor(a)))
    def _A_setup():
        B, S, D = 1, 2048, 640
        ks = 4
        return {
            "q": _w((lambda *s: torch.randn(*s, dtype=torch.bfloat16) * 0.05)(B, S, D)),
            "k": _w((lambda *s: torch.randn(*s, dtype=torch.bfloat16) * 0.2)(B, S, D)),
            "v": _w((lambda *s: torch.randn(*s, dtype=torch.bfloat16) * 0.2)(B, S, D)),
            "shift_k": _w((lambda *s: torch.randn(*s, dtype=torch.bfloat16) * 0.2)(D, ks) * 0.5),
            "ssm_k": _w((lambda *s: torch.randn(*s, dtype=torch.bfloat16) * 0.8)(D, S) * (1.0 / S ** 0.5)),
            "ssm_D": _w((lambda *s: torch.randn(*s, dtype=torch.bfloat16) * 0.2)(D)),
        }
    _A_in = _A_setup()

    def _B_setup():
        B, S, D, F = 1, 2048, 640, 1536
        return {
            "x": _w((lambda *s: torch.randn(*s, dtype=torch.bfloat16) * 0.05)(B, S, D)),
            "w1": _w((lambda *s: torch.randn(*s, dtype=torch.bfloat16) * 0.4)(D, F) * (D ** -0.5)),
            "b1": _w((lambda *s: torch.randn(*s, dtype=torch.bfloat16) * 12.8)(F) * 0.01),
            "w2": _w((lambda *s: torch.randn(*s, dtype=torch.bfloat16) * 0.2)(F, D) * (F ** -0.5)),
            "b2": _w((lambda *s: torch.randn(*s, dtype=torch.bfloat16) * 3.2)(D) * 0.01),
        }
    _B_in = _B_setup()

    return {
        "A_q": _A_in["q"],
        "A_k": _A_in["k"],
        "A_v": _A_in["v"],
        "A_shift_k": _A_in["shift_k"],
        "A_ssm_k": _A_in["ssm_k"],
        "A_ssm_D": _A_in["ssm_D"],
        "B_x": _B_in["x"],
        "B_w1": _B_in["w1"],
        "B_b1": _B_in["b1"],
        "B_w2": _B_in["w2"],
        "B_b2": _B_in["b2"],
    }

def reference(A_q, A_k, A_v, A_shift_k, A_ssm_k, A_ssm_D, B_x, B_w1, B_b1, B_w2, B_b2):
    def _A_ref(q, k, v, shift_k, ssm_k, ssm_D):
        B, S, D = q.shape
        ks = shift_k.shape[-1]
        k_pad = _pad(k, ((0, 0), (ks - 1, 0), (0, 0)))
        k_shift = torch.zeros_like(k)
        for t in range(ks):
            k_shift = k_shift + k_pad[:, t:t + S, :] * shift_k[:, ks - 1 - t][None, None, :]
        kv = k_shift * v
        L = 2 * S
        kv_pad = _pad(kv, ((0, 0), (0, S), (0, 0)))
        kf_pad = _pad(ssm_k, ((0, 0), (0, S)))
        kv_f = (lambda x, axes=(-2,-1): torch.fft.rfft2(x.float(), dim=axes))(kv_pad[:, None, :, :], axes=(1, 2))
        kf_f = (lambda x, axes=(-2,-1): torch.fft.rfft2(x.float(), dim=axes))(kf_pad[:, None, :], axes=(1, 2))
        kf_f = (lambda x, *d: x.permute(*d))(kf_f, 1, 2, 0)
        y_f = kv_f * kf_f[None, :, :, :]
        y = (lambda x, s, axes=(-2,-1): torch.fft.irfft2(x, s=s, dim=axes).to(torch.bfloat16))(y_f, (1, L), axes=(1, 2))[:, 0, :S, :]
        y = y + kv * ssm_D[None, None, :]
        return q * y

    def _B_ref(x, w1, b1, w2, b2):
        h = torch.einsum("bsd,df->bsf", x, w1) + b1
        h = _gelu(h)
        return torch.einsum("bsf,fd->bsd", h, w2) + b2

    x = A_q
    xn = _layernorm(x, axis=-1)
    return x + _A_ref(xn, A_k, A_v, A_shift_k, A_ssm_k, A_ssm_D) + _B_ref(xn, B_w1, B_b1, B_w2, B_b2)
```

```cpp
#include <cuda.h>
#include <cuda_runtime.h>
#include <cuda_bf16.h>
#include <stdint.h>

namespace {

constexpr int S_ = 2048, D_ = 640, F_ = 1536;
constexpr int NCTA = 128;
#define PFX_T 700
#define PFW_T 1500
#define XSH_T 2000
#define W1_T 2500
#define KV_T 3600
#define KV_STEP 330
#define PF_T 7500
#define PF_STEP 450
#define AUG_T 5500
#define LL_SLEEP 100
#define G2_TOFF 10
#define G2_TMUL 1
#define G2_TDIV 1
#define H_AFTER_U 1
#define PAUSE1 99
#define PAUSE2 8
#define B_AFTER_U 1
#define U_SENT 1
#define KV_GATE 1
#define TL_ALL 1

__device__ __align__(1024) __nv_bfloat16 g_h[S_ * F_];
__device__ __align__(1024) __nv_bfloat16 g_u[D_ * S_];
__device__ __align__(1024) __nv_bfloat16 g_z[D_ * S_];
__device__ __align__(1024) uint4 g_pa[S_];
__device__ __align__(1024) uint4 g_pb[4 * F_ / 2];
constexpr int FL_STRIDE = 32;
constexpr int FL_DONE = 0, FL_U = 1, FL_H = 3, FL_COUNT = 3 + 4;
__device__ __align__(1024) unsigned g_flags[FL_COUNT * FL_STRIDE];
#define TL(i) do { } while (0)

constexpr int ST1_BYTES = 40960, ST1_B = 16384;
constexpr int HST = 0;
constexpr int R2A = 49152, R2B = 65536, ST2B_BYTES = 24576;
constexpr int CONV = 163840;
constexpr int CB_BYTES = 12800, CB_E = 4480, CB_O = 8640;
constexpr int RED = CONV + 2 * CB_BYTES, RED_P = 4224, RED_BUF = 4 * RED_P;
constexpr int AUG_B = RED + RED_BUF + 512, AUG_A = AUG_B + 6144, CS_TMP = AUG_A + 4096;
constexpr int KV_K = CONV, KV_V = CONV + 22400, XSH = AUG_B;
constexpr int FIN_X = CONV, FIN_Z = CONV + 20480;
constexpr int SSTAT = XSH + 20480;
constexpr int SHK = SSTAT + 1024;
constexpr int BARS = SHK + 2560;
constexpr int SMEM_BYTES = BARS + 640;
static_assert(SMEM_BYTES <= 232448 && SSTAT >= RED + 2 * RED_BUF && KV_V + 20480 <= AUG_B && CS_TMP + 3840 <= SSTAT, "smem");
static_assert(FIN_Z % 1024 == 0 && CONV % 1024 == 0 && RED % 128 == 0, "align");
enum { B_FULL1 = 0, B_FULL2 = 4, B_HRD = 11, B_FINX = 12, B_XSH = 13, B_KV = 14, B_HRDY = 15,
       B_CNT2 = 18, B_AUG = 18, B_CFULL = 19,
       B_CNT4 = 21, B_HCH = 21, B_CEMPTY = 27, B_BASE = 29, B_RFULL = 30, B_RDONE = 46, B_XFREE = 47, B_KVFREE = 48,
       B_UFULL = 49, B_PUB2 = 50, B_EMPTY2 = 51, B_EOFREE = 56, B_PUB1 = 58,
       B_CNT8 = 59, B_EMPTY1 = 59, B_G1DONE = 63, B_G1MAIN = 64, B_REMPTY = 65, B_G1P1 = 67, B_TOK = 68, B_COUNT = 78 };

__device__ __forceinline__ uint32_t smem_u32(const void* p) { return (uint32_t)__cvta_generic_to_shared(p); }
__device__ __forceinline__ uint64_t mk_desc(uint32_t addr, uint32_t lbo, uint32_t sbo, uint32_t swz) {
  return (uint64_t)((addr & 0x3FFFF) >> 4) | ((uint64_t)(lbo >> 4) << 16) | ((uint64_t)(sbo >> 4) << 32) | ((uint64_t)swz << 62);
}
__device__ __forceinline__ void wg_fence() { asm volatile("wgmma.fence.sync.aligned;\n" ::: "memory"); }
__device__ __forceinline__ void wg_commit() { asm volatile("wgmma.commit_group.sync.aligned;\n" ::: "memory"); }
template <int N> __device__ __forceinline__ void wg_wait() { asm volatile("wgmma.wait_group.sync.aligned %0;\n" ::"n"(N) : "memory"); }
__device__ __forceinline__ void mbar_init(uint32_t b, int c) { asm volatile("mbarrier.init.shared::cta.b64 [%0], %1;\n" ::"r"(b), "r"(c) : "memory"); }
__device__ __forceinline__ void mbar_expect(uint32_t b, int bytes) {
  asm volatile("mbarrier.arrive.expect_tx.shared::cta.b64 _, [%0], %1;\n" ::"r"(b), "r"(bytes) : "memory");
}
__device__ __forceinline__ void mbar_arrive(uint32_t b) { asm volatile("mbarrier.arrive.shared::cta.b64 _, [%0];\n" ::"r"(b) : "memory"); }
__device__ __forceinline__ bool mbar_try(uint32_t b, int par) {
  uint32_t ok;
  asm volatile("{\n.reg .pred p;\nmbarrier.try_wait.parity.shared::cta.b64 p, [%1], %2;\nselp.u32 %0, 1, 0, p;\n}\n"
               : "=r"(ok) : "r"(b), "r"(par) : "memory");
  return ok;
}
__device__ __forceinline__ bool mbar_try_nb(uint32_t b, int par) {
  uint32_t ok;
  asm volatile("{\n.reg .pred p;\nmbarrier.test_wait.parity.shared::cta.b64 p, [%1], %2;\nselp.u32 %0, 1, 0, p;\n}\n"
               : "=r"(ok) : "r"(b), "r"(par) : "memory");
  return ok;
}
__device__ __forceinline__ void mbar_wait(uint32_t b, int par) {
  asm volatile(
      "{\n.reg .pred p;\n.reg .u32 n;\nmov.u32 n, 0;\n"
      "WAIT_LOOP:\n"
      "mbarrier.try_wait.parity.shared::cta.b64 p, [%0], %1;\n"
      "@p bra WAIT_DONE;\n"
      "add.u32 n, n, 1;\n"
      "setp.lt.u32 p, n, 4096;\n"
      "@p bra WAIT_LOOP;\n"
      "WAIT_DONE:\n}\n" ::"r"(b), "r"(par) : "memory");
}
__device__ __forceinline__ bool elect_one() {
  uint32_t p;
  asm volatile("{\n.reg .pred q;\nelect.sync _|q, 0xffffffff;\nselp.u32 %0, 1, 0, q;\n}\n" : "=r"(p));
  return p;
}
__device__ __forceinline__ void fence_async() { asm volatile("fence.proxy.async.global;\n" ::: "memory"); }
__device__ __forceinline__ void fence_async_smem() { asm volatile("fence.proxy.async.shared::cta;\n" ::: "memory"); }
__device__ __forceinline__ void bar_sync(int id, int n) { asm volatile("bar.sync %0, %1;\n" ::"r"(id), "r"(n) : "memory"); }
__device__ __forceinline__ void tma2d(uint32_t dst, const CUtensorMap* m, int c0, int c1, uint32_t bar) {
  asm volatile("cp.async.bulk.tensor.2d.shared::cluster.global.mbarrier::complete_tx::bytes [%0], [%1, {%3, %4}], [%2];\n"
               ::"r"(dst), "l"(m), "r"(bar), "r"(c0), "r"(c1) : "memory");
}
__device__ __forceinline__ void tma3d(uint32_t dst, const CUtensorMap* m, int c0, int c1, int c2, uint32_t bar) {
  asm volatile("cp.async.bulk.tensor.3d.shared::cluster.global.mbarrier::complete_tx::bytes [%0], [%1, {%3, %4, %5}], [%2];\n"
               ::"r"(dst), "l"(m), "r"(bar), "r"(c0), "r"(c1), "r"(c2) : "memory");
}
__device__ __forceinline__ void tma2d_store(const CUtensorMap* m, int c0, int c1, uint32_t src) {
  asm volatile("cp.async.bulk.tensor.2d.global.shared::cta.bulk_group [%0, {%2, %3}], [%1];\n"
               ::"l"(m), "r"(src), "r"(c0), "r"(c1) : "memory");
}
__device__ __forceinline__ void tma3d_store(const CUtensorMap* m, int c0, int c1, int c2, uint32_t src) {
  asm volatile("cp.async.bulk.tensor.3d.global.shared::cta.bulk_group [%0, {%2, %3, %4}], [%1];\n"
               ::"l"(m), "r"(src), "r"(c0), "r"(c1), "r"(c2) : "memory");
}
__device__ __forceinline__ void bulk_g2s(uint32_t dst, const void* src, int bytes, uint32_t bar) {
  asm volatile("cp.async.bulk.shared::cluster.global.mbarrier::complete_tx::bytes [%0], [%1], %2, [%3];\n"
               ::"r"(dst), "l"(src), "r"(bytes), "r"(bar) : "memory");
}
__device__ __forceinline__ void bulk_s2g(void* dst, uint32_t src, int bytes) {
  asm volatile("cp.async.bulk.global.shared::cta.bulk_group [%0], [%1], %2;\n" ::"l"(dst), "r"(src), "r"(bytes) : "memory");
}
__device__ __forceinline__ void bulk_commit() { asm volatile("cp.async.bulk.commit_group;\n" ::: "memory"); }
template <int N> __device__ __forceinline__ void bulk_wait() { asm volatile("cp.async.bulk.wait_group %0;\n" ::"n"(N) : "memory"); }
template <int N> __device__ __forceinline__ void bulk_wait_read() { asm volatile("cp.async.bulk.wait_group.read %0;\n" ::"n"(N) : "memory"); }
__device__ __forceinline__ void l2_prefetch(const void* p, int bytes) {
  asm volatile("cp.async.bulk.prefetch.L2.global [%0], %1;\n" ::"l"(p), "r"(bytes) : "memory");
}
__device__ __forceinline__ void wait_until(unsigned t) {
  while ((int)(clock() - t) < 0) __nanosleep(64);
}
__device__ __forceinline__ void prefetch_l2(const void* p) { asm volatile("prefetch.global.L2 [%0];\n" ::"l"(p) : "memory"); }
__device__ __forceinline__ void tmap_prefetch(const CUtensorMap* m) { asm volatile("prefetch.tensormap [%0];\n" ::"l"(m) : "memory"); }
__device__ __forceinline__ void flag_arrive(int idx) {
  asm volatile("red.release.gpu.global.add.u32 [%0], 1;\n" ::"l"(g_flags + idx * FL_STRIDE) : "memory");
}
__device__ __forceinline__ unsigned flag_ld(int idx) {
  unsigned v;
  asm volatile("ld.acquire.gpu.global.u32 %0, [%1];\n" : "=r"(v) : "l"(g_flags + idx * FL_STRIDE) : "memory");
  return v;
}
__device__ __forceinline__ unsigned flag_ld_relaxed(int idx) {
  unsigned v;
  asm volatile("ld.relaxed.gpu.global.u32 %0, [%1];\n" : "=r"(v) : "l"(g_flags + idx * FL_STRIDE) : "memory");
  return v;
}
__device__ __forceinline__ void flag_arrive_relaxed(int idx) {
  asm volatile("red.relaxed.gpu.global.add.u32 [%0], 1;\n" ::"l"(g_flags + idx * FL_STRIDE) : "memory");
}
__device__ __forceinline__ void flag_wait(int idx, unsigned target) {
#pragma unroll 1
  for (int it = 0; it < (1 << 16); it++) { if ((int)(flag_ld_relaxed(idx) - target) >= 0) break; __nanosleep(40); }
  (void)flag_ld(idx);
}
__device__ __forceinline__ unsigned read_epoch() {
  unsigned v;
  asm volatile("ld.relaxed.gpu.global.u32 %0, [%1];\n" : "=r"(v) : "l"(g_flags + FL_DONE * FL_STRIDE) : "memory");
  return (v >> 7) + 1;
}
__device__ __forceinline__ uint32_t lds32(uint32_t a) { uint32_t r; asm volatile("ld.shared.u32 %0, [%1];\n" : "=r"(r) : "r"(a) : "memory"); return r; }
__device__ __forceinline__ float2 lds64f(uint32_t a) {
  float2 r; asm volatile("ld.shared.v2.f32 {%0, %1}, [%2];\n" : "=f"(r.x), "=f"(r.y) : "r"(a) : "memory"); return r;
}
__device__ __forceinline__ uint4 lds128(uint32_t a) {
  uint4 r; asm volatile("ld.shared.v4.u32 {%0, %1, %2, %3}, [%4];\n" : "=r"(r.x), "=r"(r.y), "=r"(r.z), "=r"(r.w) : "r"(a) : "memory"); return r;
}
__device__ __forceinline__ void sts64f(uint32_t a, float x, float y) { asm volatile("st.shared.v2.f32 [%0], {%1, %2};\n" ::"r"(a), "f"(x), "f"(y) : "memory"); }
__device__ __forceinline__ void sts32f(uint32_t a, float x) { asm volatile("st.shared.f32 [%0], %1;\n" ::"r"(a), "f"(x) : "memory"); }
__device__ __forceinline__ void sts128(uint32_t a, uint32_t x, uint32_t y, uint32_t z, uint32_t w) {
  asm volatile("st.shared.v4.u32 [%0], {%1, %2, %3, %4};\n" ::"r"(a), "r"(x), "r"(y), "r"(z), "r"(w) : "memory");
}
__device__ __forceinline__ void stsm4(uint32_t a, uint32_t r0, uint32_t r1, uint32_t r2, uint32_t r3) {
  asm volatile("stmatrix.sync.aligned.m8n8.x4.shared.b16 [%0], {%1, %2, %3, %4};\n" ::"r"(a), "r"(r0), "r"(r1), "r"(r2), "r"(r3) : "memory");
}
__device__ __forceinline__ void stsm4t(uint32_t a, uint32_t r0, uint32_t r1, uint32_t r2, uint32_t r3) {
  asm volatile("stmatrix.sync.aligned.m8n8.x4.trans.shared.b16 [%0], {%1, %2, %3, %4};\n" ::"r"(a), "r"(r0), "r"(r1), "r"(r2), "r"(r3) : "memory");
}
__device__ __forceinline__ void ldsm4(uint32_t a, uint32_t* r) {
  asm volatile("ldmatrix.sync.aligned.m8n8.x4.shared.b16 {%0, %1, %2, %3}, [%4];\n"
               : "=r"(r[0]), "=r"(r[1]), "=r"(r[2]), "=r"(r[3]) : "r"(a) : "memory");
}
__device__ __forceinline__ void ldsm4t(uint32_t a, uint32_t* r) {
  asm volatile("ldmatrix.sync.aligned.m8n8.x4.trans.shared.b16 {%0, %1, %2, %3}, [%4];\n"
               : "=r"(r[0]), "=r"(r[1]), "=r"(r[2]), "=r"(r[3]) : "r"(a) : "memory");
}
__device__ __forceinline__ uint32_t pack_bf16(float lo, float hi) {
  uint32_t r; asm("cvt.rn.bf16x2.f32 %0, %1, %2;\n" : "=r"(r) : "f"(hi), "f"(lo)); return r;
}
__device__ __forceinline__ float bf_lo(uint32_t v) { return __uint_as_float(v << 16); }
__device__ __forceinline__ float bf_hi(uint32_t v) { return __uint_as_float(v & 0xffff0000u); }
__device__ __forceinline__ float bf_round(float x) { return bf_lo(pack_bf16(x, 0.f)); }
__device__ __forceinline__ uint32_t bmul2(uint32_t a, uint32_t b) { uint32_t r; asm("mul.rn.bf16x2 %0, %1, %2;\n" : "=r"(r) : "r"(a), "r"(b)); return r; }
__device__ __forceinline__ uint32_t bfma2(uint32_t a, uint32_t b, uint32_t c) {
  uint32_t r; asm("fma.rn.bf16x2 %0, %1, %2, %3;\n" : "=r"(r) : "r"(a), "r"(b), "r"(c)); return r;
}
__device__ __forceinline__ float tanh_fast(float x) { float r; asm("tanh.approx.f32 %0, %1;\n" : "=f"(r) : "f"(x)); return r; }
__device__ __forceinline__ uint4 ldg128(const void* p) {
  uint4 r; asm volatile("ld.global.nc.L1::no_allocate.v4.u32 {%0, %1, %2, %3}, [%4];\n" : "=r"(r.x), "=r"(r.y), "=r"(r.z), "=r"(r.w) : "l"(p)); return r;
}
__device__ __forceinline__ uint32_t ldg32(const void* p) {
  uint32_t r; asm volatile("ld.global.nc.L1::no_allocate.u32 %0, [%1];\n" : "=r"(r) : "l"(p)); return r;
}
__device__ __forceinline__ uint4 ld_pkt(const uint4* p) {
  uint4 r;
  asm volatile("{\n.reg .b128 t;\n.reg .b64 a, b;\nld.relaxed.gpu.global.b128 t, [%4];\nmov.b128 {a, b}, t;\nmov.b64 {%0, %1}, a;\nmov.b64 {%2, %3}, b;\n}\n"
               : "=r"(r.x), "=r"(r.y), "=r"(r.z), "=r"(r.w) : "l"(p) : "memory");
  return r;
}
__device__ __forceinline__ void st_pkt(uint4* p, uint32_t x, uint32_t y, uint32_t z, uint32_t w) {
  asm volatile("{\n.reg .b128 t;\n.reg .b64 a, b;\nmov.b64 a, {%1, %2};\nmov.b64 b, {%3, %4};\nmov.b128 t, {a, b};\nst.relaxed.gpu.global.b128 [%0], t;\n}\n"
               ::"l"(p), "r"(x), "r"(y), "r"(z), "r"(w) : "memory");
}
__device__ __forceinline__ uint32_t tag_bits(unsigned ep) { return (ep & 1u) | ((ep & 2u) << 15); }
__device__ __forceinline__ void st_tagged(void* p, uint32_t x, uint32_t y, uint32_t z, uint32_t w, uint32_t tag) {
  st_pkt(reinterpret_cast<uint4*>(p), (x & ~0x00010001u) | tag, y, z, w);
}
template <int N> __device__ __forceinline__ void ld_tagged(uint4* r, const __nv_bfloat16* p, int stride, uint32_t tag) {
#pragma unroll
  for (int i = 0; i < N; i++) r[i].x = ~tag;
#pragma unroll 1
  for (int it = 0; it < (1 << 12); it++) {
    uint32_t bad = 0;
#pragma unroll
    for (int i = 0; i < N; i++)
      if ((r[i].x ^ tag) & 0x00010001u) r[i] = ld_pkt(reinterpret_cast<const uint4*>(p + i * stride));
#pragma unroll
    for (int i = 0; i < N; i++) bad |= r[i].x ^ tag;
    if (!__any_sync(~0u, bad & 0x00010001u)) break;
    __nanosleep(LL_SLEEP);
  }
}
__device__ __forceinline__ float2 ldcg64f(const void* p) {
  float2 r; asm volatile("ld.global.cg.v2.f32 {%0, %1}, [%2];\n" : "=f"(r.x), "=f"(r.y) : "l"(p) : "memory"); return r;
}
__device__ __forceinline__ void stg128(void* p, uint32_t x, uint32_t y, uint32_t z, uint32_t w) {
  asm volatile("st.global.v4.u32 [%0], {%1, %2, %3, %4};\n" ::"l"(p), "r"(x), "r"(y), "r"(z), "r"(w) : "memory");
}

__device__ __forceinline__ void wgmma_rs_n32_init(float* d, const uint32_t* a, uint64_t db) {
  asm volatile("{\n.reg .pred p;\nsetp.ne.b32 p, 0, 0;\n"
    "wgmma.mma_async.sync.aligned.m64n32k16.f32.bf16.bf16 {%0, %1, %2, %3, %4, %5, %6, %7, %8, %9, %10, %11, %12, %13, %14, %15}, {%16, %17, %18, %19}, %20, p, 1, 1, 0;\n}\n"
    : "=f"(d[0]), "=f"(d[1]), "=f"(d[2]), "=f"(d[3]), "=f"(d[4]), "=f"(d[5]), "=f"(d[6]), "=f"(d[7]), "=f"(d[8]), "=f"(d[9]), "=f"(d[10]), "=f"(d[11]), "=f"(d[12]), "=f"(d[13]), "=f"(d[14]), "=f"(d[15])
    : "r"(a[0]), "r"(a[1]), "r"(a[2]), "r"(a[3]), "l"(db));
}
__device__ __forceinline__ void wgmma_n192_bmn(float* d, uint64_t da, uint64_t db, int sc) {
  asm volatile("{\n.reg .pred p;\nsetp.ne.b32 p, %98, 0;\n"
    "wgmma.mma_async.sync.aligned.m64n192k16.f32.bf16.bf16 {%0, %1, %2, %3, %4, %5, %6, %7, %8, %9, %10, %11, %12, %13, %14, %15, %16, %17, %18, %19, %20, %21, %22, %23, %24, %25, %26, %27, %28, %29, %30, %31, %32, %33, %34, %35, %36, %37, %38, %39, %40, %41, %42, %43, %44, %45, %46, %47, %48, %49, %50, %51, %52, %53, %54, %55, %56, %57, %58, %59, %60, %61, %62, %63, %64, %65, %66, %67, %68, %69, %70, %71, %72, %73, %74, %75, %76, %77, %78, %79, %80, %81, %82, %83, %84, %85, %86, %87, %88, %89, %90, %91, %92, %93, %94, %95}, %96, %97, p, 1, 1, 0, 1;\n}\n"
    : "+f"(d[0]), "+f"(d[1]), "+f"(d[2]), "+f"(d[3]), "+f"(d[4]), "+f"(d[5]), "+f"(d[6]), "+f"(d[7]), "+f"(d[8]), "+f"(d[9]), "+f"(d[10]), "+f"(d[11]), "+f"(d[12]), "+f"(d[13]), "+f"(d[14]), "+f"(d[15]), "+f"(d[16]), "+f"(d[17]), "+f"(d[18]), "+f"(d[19]), "+f"(d[20]), "+f"(d[21]), "+f"(d[22]), "+f"(d[23]), "+f"(d[24]), "+f"(d[25]), "+f"(d[26]), "+f"(d[27]), "+f"(d[28]), "+f"(d[29]), "+f"(d[30]), "+f"(d[31]), "+f"(d[32]), "+f"(d[33]), "+f"(d[34]), "+f"(d[35]), "+f"(d[36]), "+f"(d[37]), "+f"(d[38]), "+f"(d[39]), "+f"(d[40]), "+f"(d[41]), "+f"(d[42]), "+f"(d[43]), "+f"(d[44]), "+f"(d[45]), "+f"(d[46]), "+f"(d[47]), "+f"(d[48]), "+f"(d[49]), "+f"(d[50]), "+f"(d[51]), "+f"(d[52]), "+f"(d[53]), "+f"(d[54]), "+f"(d[55]), "+f"(d[56]), "+f"(d[57]), "+f"(d[58]), "+f"(d[59]), "+f"(d[60]), "+f"(d[61]), "+f"(d[62]), "+f"(d[63]), "+f"(d[64]), "+f"(d[65]), "+f"(d[66]), "+f"(d[67]), "+f"(d[68]), "+f"(d[69]), "+f"(d[70]), "+f"(d[71]), "+f"(d[72]), "+f"(d[73]), "+f"(d[74]), "+f"(d[75]), "+f"(d[76]), "+f"(d[77]), "+f"(d[78]), "+f"(d[79]), "+f"(d[80]), "+f"(d[81]), "+f"(d[82]), "+f"(d[83]), "+f"(d[84]), "+f"(d[85]), "+f"(d[86]), "+f"(d[87]), "+f"(d[88]), "+f"(d[89]), "+f"(d[90]), "+f"(d[91]), "+f"(d[92]), "+f"(d[93]), "+f"(d[94]), "+f"(d[95])
    : "l"(da), "l"(db), "r"(sc));
}
__device__ __forceinline__ void wgmma_n192_bk(float* d, uint64_t da, uint64_t db, int sc) {
  asm volatile("{\n.reg .pred p;\nsetp.ne.b32 p, %98, 0;\n"
    "wgmma.mma_async.sync.aligned.m64n192k16.f32.bf16.bf16 {%0, %1, %2, %3, %4, %5, %6, %7, %8, %9, %10, %11, %12, %13, %14, %15, %16, %17, %18, %19, %20, %21, %22, %23, %24, %25, %26, %27, %28, %29, %30, %31, %32, %33, %34, %35, %36, %37, %38, %39, %40, %41, %42, %43, %44, %45, %46, %47, %48, %49, %50, %51, %52, %53, %54, %55, %56, %57, %58, %59, %60, %61, %62, %63, %64, %65, %66, %67, %68, %69, %70, %71, %72, %73, %74, %75, %76, %77, %78, %79, %80, %81, %82, %83, %84, %85, %86, %87, %88, %89, %90, %91, %92, %93, %94, %95}, %96, %97, p, 1, 1, 0, 0;\n}\n"
    : "+f"(d[0]), "+f"(d[1]), "+f"(d[2]), "+f"(d[3]), "+f"(d[4]), "+f"(d[5]), "+f"(d[6]), "+f"(d[7]), "+f"(d[8]), "+f"(d[9]), "+f"(d[10]), "+f"(d[11]), "+f"(d[12]), "+f"(d[13]), "+f"(d[14]), "+f"(d[15]), "+f"(d[16]), "+f"(d[17]), "+f"(d[18]), "+f"(d[19]), "+f"(d[20]), "+f"(d[21]), "+f"(d[22]), "+f"(d[23]), "+f"(d[24]), "+f"(d[25]), "+f"(d[26]), "+f"(d[27]), "+f"(d[28]), "+f"(d[29]), "+f"(d[30]), "+f"(d[31]), "+f"(d[32]), "+f"(d[33]), "+f"(d[34]), "+f"(d[35]), "+f"(d[36]), "+f"(d[37]), "+f"(d[38]), "+f"(d[39]), "+f"(d[40]), "+f"(d[41]), "+f"(d[42]), "+f"(d[43]), "+f"(d[44]), "+f"(d[45]), "+f"(d[46]), "+f"(d[47]), "+f"(d[48]), "+f"(d[49]), "+f"(d[50]), "+f"(d[51]), "+f"(d[52]), "+f"(d[53]), "+f"(d[54]), "+f"(d[55]), "+f"(d[56]), "+f"(d[57]), "+f"(d[58]), "+f"(d[59]), "+f"(d[60]), "+f"(d[61]), "+f"(d[62]), "+f"(d[63]), "+f"(d[64]), "+f"(d[65]), "+f"(d[66]), "+f"(d[67]), "+f"(d[68]), "+f"(d[69]), "+f"(d[70]), "+f"(d[71]), "+f"(d[72]), "+f"(d[73]), "+f"(d[74]), "+f"(d[75]), "+f"(d[76]), "+f"(d[77]), "+f"(d[78]), "+f"(d[79]), "+f"(d[80]), "+f"(d[81]), "+f"(d[82]), "+f"(d[83]), "+f"(d[84]), "+f"(d[85]), "+f"(d[86]), "+f"(d[87]), "+f"(d[88]), "+f"(d[89]), "+f"(d[90]), "+f"(d[91]), "+f"(d[92]), "+f"(d[93]), "+f"(d[94]), "+f"(d[95])
    : "l"(da), "l"(db), "r"(sc));
}
__device__ __forceinline__ void wgmma_n160_bmn(float* d, uint64_t da, uint64_t db, int sc) {
  asm volatile("{\n.reg .pred p;\nsetp.ne.b32 p, %82, 0;\n"
    "wgmma.mma_async.sync.aligned.m64n160k16.f32.bf16.bf16 {%0, %1, %2, %3, %4, %5, %6, %7, %8, %9, %10, %11, %12, %13, %14, %15, %16, %17, %18, %19, %20, %21, %22, %23, %24, %25, %26, %27, %28, %29, %30, %31, %32, %33, %34, %35, %36, %37, %38, %39, %40, %41, %42, %43, %44, %45, %46, %47, %48, %49, %50, %51, %52, %53, %54, %55, %56, %57, %58, %59, %60, %61, %62, %63, %64, %65, %66, %67, %68, %69, %70, %71, %72, %73, %74, %75, %76, %77, %78, %79}, %80, %81, p, 1, 1, 0, 1;\n}\n"
    : "+f"(d[0]), "+f"(d[1]), "+f"(d[2]), "+f"(d[3]), "+f"(d[4]), "+f"(d[5]), "+f"(d[6]), "+f"(d[7]), "+f"(d[8]), "+f"(d[9]), "+f"(d[10]), "+f"(d[11]), "+f"(d[12]), "+f"(d[13]), "+f"(d[14]), "+f"(d[15]), "+f"(d[16]), "+f"(d[17]), "+f"(d[18]), "+f"(d[19]), "+f"(d[20]), "+f"(d[21]), "+f"(d[22]), "+f"(d[23]), "+f"(d[24]), "+f"(d[25]), "+f"(d[26]), "+f"(d[27]), "+f"(d[28]), "+f"(d[29]), "+f"(d[30]), "+f"(d[31]), "+f"(d[32]), "+f"(d[33]), "+f"(d[34]), "+f"(d[35]), "+f"(d[36]), "+f"(d[37]), "+f"(d[38]), "+f"(d[39]), "+f"(d[40]), "+f"(d[41]), "+f"(d[42]), "+f"(d[43]), "+f"(d[44]), "+f"(d[45]), "+f"(d[46]), "+f"(d[47]), "+f"(d[48]), "+f"(d[49]), "+f"(d[50]), "+f"(d[51]), "+f"(d[52]), "+f"(d[53]), "+f"(d[54]), "+f"(d[55]), "+f"(d[56]), "+f"(d[57]), "+f"(d[58]), "+f"(d[59]), "+f"(d[60]), "+f"(d[61]), "+f"(d[62]), "+f"(d[63]), "+f"(d[64]), "+f"(d[65]), "+f"(d[66]), "+f"(d[67]), "+f"(d[68]), "+f"(d[69]), "+f"(d[70]), "+f"(d[71]), "+f"(d[72]), "+f"(d[73]), "+f"(d[74]), "+f"(d[75]), "+f"(d[76]), "+f"(d[77]), "+f"(d[78]), "+f"(d[79])
    : "l"(da), "l"(db), "r"(sc));
}
__device__ __forceinline__ void wgmma_rs_n32(float* d, const uint32_t* a, uint64_t db, int sc) {
  asm volatile("{\n.reg .pred p;\nsetp.ne.b32 p, %21, 0;\n"
    "wgmma.mma_async.sync.aligned.m64n32k16.f32.bf16.bf16 {%0, %1, %2, %3, %4, %5, %6, %7, %8, %9, %10, %11, %12, %13, %14, %15}, {%16, %17, %18, %19}, %20, p, 1, 1, 0;\n}\n"
    : "+f"(d[0]), "+f"(d[1]), "+f"(d[2]), "+f"(d[3]), "+f"(d[4]), "+f"(d[5]), "+f"(d[6]), "+f"(d[7]), "+f"(d[8]), "+f"(d[9]), "+f"(d[10]), "+f"(d[11]), "+f"(d[12]), "+f"(d[13]), "+f"(d[14]), "+f"(d[15])
    : "r"(a[0]), "r"(a[1]), "r"(a[2]), "r"(a[3]), "l"(db), "r"(sc));
}

__device__ __forceinline__ float gelu_scaled(float acc, float hr) {
  const float hv = acc * hr;
  const float p = fmaf(hv * hv, 8.f * 0.7978845608028654f * 0.044715f, 2.f * 0.7978845608028654f);
  return fmaf(hv, tanh_fast(hv * p), hv);
}
template <int M> __device__ __forceinline__ void conv_frag(uint32_t* f, uint32_t abase) {
  const uint32_t a = abase + 256 * M;
  f[0] = lds32(a); f[1] = lds32(a + 128); f[2] = lds32(a + 16); f[3] = lds32(a + 144);
}
constexpr uint32_t ONE2 = 0x3f803f80u;
#define TBLK(p) ((p) < 8 ? ((p) >> 1) + rot : (rot ? 0 : 4))

struct Params {
  CUtensorMap x_a, w1, kt, vt, h, w2, w2h, x_t, out;
  const __nv_bfloat16 *x, *k, *v, *shift_k, *ssm_k, *ssm_D, *w1p, *b1, *w2p, *b2;
};

__global__ void __launch_bounds__(512, 1) fused_kernel(const __grid_constant__ Params P) {
  extern __shared__ __align__(1024) uint8_t smem[];
  const uint32_t sb = smem_u32(smem);
  const int tid = threadIdx.x, lane = tid & 31;
  const int warp = __shfl_sync(~0u, tid >> 5, 0), wg = warp >> 2;
  const int b = blockIdx.x;
  const int strip = b >> 5, slice = (b >> 2) & 7;
  const int rb128 = 4 * strip + (b & 3);
  const int rb64 = 2 * rb128 + (slice >> 2), ns = slice & 3;
  const int rot = ns & 1;
#define BAR(i) (sb + BARS + 8 * (i))
  const unsigned t0 = clock();

  if (warp == 12) {
    if (elect_one()) {
#pragma unroll
      for (int i = 0; i < 4; i++) mbar_init(BAR(B_FULL1 + i), 1);
      asm volatile("fence.mbarrier_init.release.cluster;\n" ::: "memory");
    }
#pragma unroll 1
    for (int kt = 0; kt < 4; kt++) {
      if (elect_one()) {
        mbar_expect(BAR(B_FULL1 + kt), ST1_BYTES);
        tma2d(sb + kt * ST1_BYTES, &P.x_a, kt * 64, rb128 * 128, BAR(B_FULL1 + kt));
        tma3d(sb + kt * ST1_BYTES + ST1_B, &P.w1, 0, kt * 64, slice * 3, BAR(B_FULL1 + kt));
      }
    }
  } else if (warp == 13) {
    if (lane < 9) asm volatile("prefetch.L2 [%0];\n" ::"l"(&P.x_a + lane) : "memory");
    const __nv_bfloat16* w1s = P.w1p + 2 * b * F_ + lane * 64;
    const __nv_bfloat16* xs = P.x + (128 * rb128 + 16 * slice + (lane >> 1)) * D_ + (lane & 1) * 64;
    prefetch_l2(xs);
    prefetch_l2(w1s);
    prefetch_l2(xs + 128);
    if (lane < 16) prefetch_l2(w1s + 2048);
  } else if (warp < 8) {
#pragma unroll 1
    for (int i = 4 + warp; i < B_COUNT; i += 8)
      if (elect_one()) mbar_init(BAR(i), i >= B_TOK ? 1 : 1 << ((i >= B_CNT2) + (i >= B_CNT4) + (i >= B_CNT8)));
    asm volatile("fence.mbarrier_init.release.cluster;\n" ::: "memory");
  }

  if (wg == 3) {
    asm volatile("setmaxnreg.dec.sync.aligned.u32 64;\n");
    bar_sync(0, 512);
    if (warp == 12) {
#pragma unroll 1
      for (int kt = 4; kt < 10; kt++) {
        const int s = kt & 3;
        mbar_wait(BAR(B_EMPTY1 + s), kt >> 3);
        if (elect_one()) {
          TL(104 + kt);
          mbar_expect(BAR(B_FULL1 + s), ST1_BYTES);
          tma2d(sb + s * ST1_BYTES, &P.x_a, kt * 64, rb128 * 128, BAR(B_FULL1 + s));
          tma3d(sb + s * ST1_BYTES + ST1_B, &P.w1, 0, kt * 64, slice * 3, BAR(B_FULL1 + s));
        }
      }
      const int nb0 = (160 * ns + 32 * rot) >> 6;
      const int nrem = 160 * ns + (rot ? 0 : 128);
      const uint32_t own = sb + HST + (rb64 & 1) * 3 * 8192, oth = sb + HST + ((rb64 & 1) ^ 1) * 3 * 8192;
      int k0 = slice * 192, s = 0, par = 1;
      mbar_wait(BAR(B_G1DONE), 0);
      if (B_AFTER_U) mbar_wait(BAR(B_UFULL), 0);
#pragma unroll 1
      for (int kt = 0; kt < 24; kt++) {
        mbar_wait(BAR(B_EMPTY2 + s), par);
        if (kt == 4) { mbar_wait(BAR(B_HRD), 0); mbar_wait(BAR(B_EMPTY2 + 2), 0); }
        const uint32_t bs = s == 4 ? own : sb + R2B + s * ST2B_BYTES;
        if (elect_one()) {
          mbar_expect(BAR(B_FULL2 + s), kt < 3 ? 20480 : 20480 + 8192);
          tma3d(bs, &P.w2, 0, k0, nb0, BAR(B_FULL2 + s));
          tma2d(bs + 16384, &P.w2h, nrem, k0, BAR(B_FULL2 + s));
        }
        if (kt >= 3) {
          if (kt == 3) {
            mbar_wait(BAR(B_HRDY), 0);
            fence_async();
            if (lane == 0) TL(2);
          }
          if (elect_one()) {
            if (kt >= 8 && kt < 21) TL(106 + kt);
            tma2d(s < 3 ? oth + s * 8192 : sb + R2A + (s - 3) * 8192, &P.h, k0, rb64 * 64, BAR(B_FULL2 + s));
          }
        }
        if (kt < 2) k0 += 64;
        else if (kt == 2) k0 = slice == 0 ? 192 : 0;
        else {
          k0 += 192;
          if ((unsigned)(k0 - slice * 192) < 192u) k0 += 192;
          if (k0 >= F_) k0 -= slice == 0 ? F_ - 256 : F_ - 64;
        }
        if (++s == 5) { s = 0; par ^= 1; }
      }
    } else if (warp == 13) {
      {
        const __nv_bfloat16* xs = P.x + (128 * rb128 + 16 * slice + (lane >> 1)) * D_ + 256 + (lane & 1) * 64;
        wait_until(t0 + PFX_T);
        prefetch_l2(xs); prefetch_l2(xs + 128); prefetch_l2(xs + 256);
        const __nv_bfloat16* w1s = P.w1p + (256 + 3 * b) * F_ + lane * 64;
        wait_until(t0 + PFW_T);
        prefetch_l2(w1s); prefetch_l2(w1s + 2048);
        if (lane < 8) prefetch_l2(w1s + 4096);
        wait_until(t0 + XSH_T);
        if (lane == 0) TL(57);
        if (elect_one()) {
          mbar_expect(BAR(B_XSH), 20480);
          bulk_g2s(sb + XSH, P.x + (128 * rb128 + 16 * slice) * D_, 20480, BAR(B_XSH));
          mbar_expect(BAR(B_KV), 22400 + 20480 + 2560);
          bulk_g2s(sb + SHK, P.shift_k + 320 * (b & 1) * 4, 2560, BAR(B_KV));
        }
      }
      if (lane == 0) TL(58);
      const int jit = (b * 37) & 127;
#pragma unroll 1
      for (int i = 0; i < 10; i++) {
        wait_until(t0 + KV_T + (jit * KV_STEP >> 7) + i * KV_STEP);
        if (elect_one())
          tma3d(sb + (i < 5 ? KV_K + i * 4480 : KV_V - 5 * 4096 + i * 4096), i < 5 ? &P.kt : &P.vt, 0, 32 * (b >> 1) - (i < 5 ? 3 : 0),
                5 * (b & 1) + (i < 5 ? i : i - 5), BAR(B_KV));
      }
      if (lane == 0) TL(39);
#pragma unroll 1
      for (int i = 0; i < 7; i++) {
        const __nv_bfloat16* p = (i >= 2 && i < 5 ? P.w2p + b * 12 * D_ + (i - 2) * 2560 : P.ssm_k + 5 * b * S_ + (i < 2 ? i : i - 3) * 2560) + lane * 64;
        wait_until(t0 + PF_T + (jit * PF_STEP >> 7) + i * PF_STEP);
        prefetch_l2(p);
        if (lane < 8) prefetch_l2(p + 2048);
      }
      const float dd = __bfloat162float(P.ssm_D[5 * b + (lane < 5 ? lane : 0)]);
      const unsigned ep = read_epoch();
#pragma unroll 1
      for (int ch = 0; ch < 5; ch++) {
        const uint32_t cb = sb + CONV + (ch & 1) * CB_BYTES;
        uint4 e[8];
        uint32_t pv[8];
#pragma unroll
        for (int r = 0; r < 8; r++) e[r] = ldg128(P.ssm_k + (5 * b + ch) * S_ + (lane + 32 * r) * 8);
        const float dch = __shfl_sync(~0u, dd, ch);
        if (lane == 0) e[0].x = (e[0].x & 0xffff0000u) | (pack_bf16(bf_lo(e[0].x) + dch, 0.f) & 0xffffu);
#pragma unroll
        for (int r = 0; r < 8; r++) pv[r] = __shfl_sync(~0u, e[r].w, (lane + 31) & 31);
        if (ch == 0) {
          mbar_wait(BAR(B_KVFREE), 0);
          if (lane < 20) {
            const int off = lane < 18 ? 4096 + lane * 16 : lane == 18 ? CB_E : CB_O;
            sts128(sb + CONV + off, 0, 0, 0, 0);
            sts128(sb + CONV + CB_BYTES + off, 0, 0, 0, 0);
            fence_async_smem();
          }
        }
        if (ch >= 2) mbar_wait(BAR(B_EOFREE + (ch & 1)), ch >> 2);
#pragma unroll
        for (int r = 7; r >= 0; r--) {
          sts128(cb + CB_E + 16 + (lane + 32 * r) * 16, e[r].x, e[r].y, e[r].z, e[r].w);
          sts128(cb + CB_O + 16 + (lane + 32 * r) * 16, __byte_perm(lane ? pv[r] : r ? pv[r ? r - 1 : 0] : 0u, e[r].x, 0x5432),
                 __byte_perm(e[r].x, e[r].y, 0x5432), __byte_perm(e[r].y, e[r].z, 0x5432), __byte_perm(e[r].z, e[r].w, 0x5432));
        }
        __syncwarp();
        if (lane < (ch < 2 ? 2 : 1)) mbar_arrive(BAR(B_CFULL + (ch & 1)));
        if (ch >= 2) {
          if (ch == 2) { flag_wait(FL_U + (b >> 6), 64 * ep); fence_async(); }
          mbar_wait(BAR(B_CEMPTY + (ch & 1)), ch >> 2);
          if (elect_one()) {
            mbar_expect(BAR(B_CFULL + (ch & 1)), 4096);
            bulk_g2s(cb, g_u + (5 * b + ch) * S_, 4096, BAR(B_CFULL + (ch & 1)));
          }
        }
      }
    } else {
      const int j = warp - 14;
      const unsigned ep = read_epoch();
      {
        uint4 pk[8];
        const uint4* pp = g_pb + slice * 96 + lane + 32 * j;
        const uint4* pa = j == 0 ? g_pa + rb128 * 128 + lane : pp;
        const int sa = j == 0 ? 32 : F_ / 2;
        if (j == 1) pp += 32;
#pragma unroll
        for (int i = 0; i < 8; i++) pk[i].w = ~ep;
        wait_until(t0 + AUG_T);
#pragma unroll 1
        for (int it = 0; it < (1 << 12); it++) {
          bool ok = true;
#pragma unroll
          for (int i = 0; i < 8; i++)
            if (pk[i].w != ep) pk[i] = ld_pkt(i < 4 ? pa + i * sa : pp + (i - 4) * (F_ / 2));
#pragma unroll
          for (int i = 0; i < 8; i++) ok = ok && pk[i].w == ep;
          if (__all_sync(~0u, ok)) break;
          __nanosleep(LL_SLEEP);
        }
        if (lane == 0 && j == 0) TL(16);
        mbar_wait(BAR(B_XFREE), 0);
        if (j == 0) {
#pragma unroll
          for (int i = 0; i < 4; i++) {
            const uint32_t hh = __byte_perm(pk[i].x, 0, 0x1010), a = sb + AUG_A + (lane >> 3) * 256 + (lane & 7) * 16 + i * 1024;
            sts128(a, hh, __byte_perm(pk[i].x, pk[i].y, 0x5432), hh, __byte_perm(pk[i].x, pk[i].y, 0x7632));
            sts128(a + 128, hh, pk[i].x >> 16, hh, pk[i].x >> 16);
            sts64f(sb + SSTAT + lane * 8 + i * 256, -(bf_lo(pk[i].x) + bf_hi(pk[i].x)), __uint_as_float(pk[i].z));
          }
        }
#pragma unroll 1
        for (int g = 1; g >= 1 - j; g--) {
          const uint32_t a = sb + AUG_B + (lane >> 2) * 256 + (lane & 3) * 32 + (j == 0 ? 0 : 2048 + 2048 * g);
          sts128(a, pk[4].x, __byte_perm(pk[4].x, pk[4].z, 0x5410), pk[5].x, __byte_perm(pk[5].x, pk[5].z, 0x5410));
          sts128(a + 128, pk[6].x, pk[6].x & 0xffffu, pk[7].x, pk[7].x & 0xffffu);
          sts128(a + 16, pk[4].y, __byte_perm(pk[4].y, pk[4].z, 0x7610), pk[5].y, __byte_perm(pk[5].y, pk[5].z, 0x7610));
          sts128(a + 144, pk[6].y, pk[6].y & 0xffffu, pk[7].y, pk[7].y & 0xffffu);
#pragma unroll
          for (int i = 0; i < 4; i++) pk[4 + i] = pk[i];
        }
        fence_async_smem();
        __syncwarp();
        if (lane == 0) { mbar_arrive(BAR(B_AUG)); if (j == 0) TL(17); }
      }
      if (j == 0) {
        if (H_AFTER_U) mbar_wait(BAR(B_UFULL), 0);
#pragma unroll 1
        for (int ch = 0; ch < 6; ch++) {
          const int g = ch & 1, c = ch >> 1;
          mbar_wait(BAR(B_HCH + 3 * g + c), 0);
          if (elect_one()) tma2d_store(&P.h, slice * 192 + c * 64, rb128 * 128 + 64 * g, sb + HST + (3 * g + c) * 8192);
        }
        if (elect_one()) {
          TL(51);
          bulk_commit();
          bulk_wait<0>();
          mbar_arrive(BAR(B_HRD));
          TL(54);
          flag_arrive(FL_H + strip);
          TL(9);
        }
      } else {
        mbar_wait(BAR(B_PUB2), 0);
        if (elect_one()) flag_arrive(FL_U + (b & 1));
        flag_wait(FL_H + strip, 32 * ep);
        if (elect_one()) mbar_arrive(BAR(B_HRDY));
      }
    }
  } else if (wg == 2) {
    asm volatile("setmaxnreg.inc.sync.aligned.u32 192;\n");
    const int t = tid & 127, w = warp & 3, b0 = lane >> 2, c = lane & 3;
    bar_sync(0, 512);
    const unsigned ep = read_epoch();
    const uint32_t tag = tag_bits(ep);
    {
      uint4 wv[8];
      const int tc = t < 120 ? t : 119, cc = tc % 6, rg = tc / 6;
      const __nv_bfloat16* wr = P.w1p + (160 * (rb128 >> 2) + 8 * rg) * F_ + slice * 192 + (rb128 & 3) * 48 + cc * 8;
      const uint32_t b1v = ldg32(P.b1 + slice * 192 + (rb128 & 3) * 48 + (t < 96 ? (t >> 2) * 2 : 0));
      wait_until(t0 + W1_T);
#pragma unroll
      for (int j = 0; j < 8; j++) wv[j] = ldg128(wr + j * F_);
      mbar_wait(BAR(B_XSH), 0);
      if (t == 0) TL(18);
      const uint32_t xsa = sb + XSH + (4 * w + (lane >> 3)) * 1280 + (lane & 7) * 16;
      uint4 xa = lds128(xsa), xb = lds128(xsa + 128);
      const uint32_t x0w = __shfl_sync(~0u, xa.x, lane & 24);
      const uint32_t nx0 = __byte_perm(x0w, 0, 0x1010) ^ 0x80008000u;
      float s4[4] = {0.f, 0.f, 0.f, 0.f}, q4[4] = {0.f, 0.f, 0.f, 0.f};
#pragma unroll 1
      for (int j = 0; j < 10; j++) {
        const uint32_t u4[4] = {xa.x, xa.y, xa.z, xa.w};
        xa = xb;
        xb = lds128(xsa + (j < 8 ? j + 2 : 0) * 128);
#pragma unroll
        for (int e = 0; e < 4; e++) {
          const uint32_t dd = bfma2(u4[e], ONE2, nx0);
          const float a0 = bf_lo(dd), a1 = bf_hi(dd);
          s4[e] += a0 + a1;
          q4[e] = fmaf(a0, a0, fmaf(a1, a1, q4[e]));
        }
      }
      __syncwarp();
      if (lane == 0) mbar_arrive(BAR(B_XFREE));
      float s = (s4[0] + s4[1]) + (s4[2] + s4[3]), q = (q4[0] + q4[1]) + (q4[2] + q4[3]);
#pragma unroll
      for (int m = 1; m < 8; m <<= 1) { s += __shfl_xor_sync(~0u, s, m); q += __shfl_xor_sync(~0u, q, m); }
      s *= 1.f / D_;
      const float mu = -(bf_lo(x0w) + s), ve = fmaxf(q * (1.f / D_) - s * s, 0.f) + 1e-5f;
      const float r0 = rsqrtf(ve), rs = r0 * fmaf(-0.5f * ve * r0, r0, 1.5f), sg = ve * rs;
      const float mh = bf_round(mu), sh = bf_round(sg);
      if ((lane & 7) == 0)
        st_pkt(g_pa + 128 * rb128 + 16 * slice + 4 * w + (lane >> 3), pack_bf16(mh, mu - mh), pack_bf16(sh, sg - sh), __float_as_uint(rs), ep);
      if (t == 0) TL(14);
      float cs[8];
#pragma unroll
      for (int e = 0; e < 8; e++) cs[e] = 0.f;
#pragma unroll
      for (int j = 0; j < 8; j++) {
        cs[0] += bf_lo(wv[j].x); cs[1] += bf_hi(wv[j].x); cs[2] += bf_lo(wv[j].y); cs[3] += bf_hi(wv[j].y);
        cs[4] += bf_lo(wv[j].z); cs[5] += bf_hi(wv[j].z); cs[6] += bf_lo(wv[j].w); cs[7] += bf_hi(wv[j].w);
      }
      mbar_wait(BAR(B_XFREE), 0);
      if (t < 120) {
        const uint32_t a = sb + CS_TMP + (rg * 48 + cc * 8) * 4;
        sts128(a, __float_as_uint(cs[0]), __float_as_uint(cs[1]), __float_as_uint(cs[2]), __float_as_uint(cs[3]));
        sts128(a + 16, __float_as_uint(cs[4]), __float_as_uint(cs[5]), __float_as_uint(cs[6]), __float_as_uint(cs[7]));
      }
      bar_sync(1, 128);
      if (w < 3) {
        float p[10];
#pragma unroll
        for (int j = 0; j < 10; j++) p[j] = __uint_as_float(lds32(sb + CS_TMP + ((2 * j + (t & 1)) * 48 + (t >> 1)) * 4));
        float g = ((p[0] + p[1]) + (p[2] + p[3])) + ((p[4] + p[5]) + (p[6] + p[7])) + (p[8] + p[9]);
        g += __shfl_xor_sync(~0u, g, 1);
        const float gh = bf_round(g);
        const uint32_t pk = pack_bf16(gh, g - gh), pk1 = __shfl_xor_sync(~0u, pk, 2);
        if ((t & 3) == 0) st_pkt(g_pb + (rb128 >> 2) * (F_ / 2) + slice * 96 + (rb128 & 3) * 24 + (t >> 2), pk, pk1, rb128 < 8 ? b1v : 0u, ep);
      }
      __syncwarp();
      if (lane == 0) mbar_arrive(BAR(B_PUB1));
      if (t == 0) TL(15);
    }
    {
      mbar_wait(BAR(B_KV), 0);
      if (KV_GATE) mbar_wait(BAR(B_G1MAIN), 0);
      if (t == 0) TL(40);
      const int rA = 8 * (lane >> 3), cA = 64 * w + 8 * (lane & 7);
      const int rB = 16 * (w >> 1) + 8 * (lane & 1), cB = 32 * (w & 1) + 2 * (lane >> 1);
      uint32_t kk[11][5], q[8][5];
      uint4 sw[5];
      {
        const uint32_t ka = sb + KV_K + w * 4480 + rA * 128 + (lane & 7) * 16, va = sb + KV_V + w * 4096 + rA * 128 + (lane & 7) * 16;
        const uint32_t kb = sb + KV_K + 4 * 4480 + rB * 128 + cB * 2, vb = sb + KV_V + 4 * 4096 + rB * 128 + cB * 2;
#define LDS4(dst, a) { const uint4 v_ = lds128(a); dst[0] = v_.x; dst[1] = v_.y; dst[2] = v_.z; dst[3] = v_.w; }
#pragma unroll
        for (int e = 0; e < 5; e++) sw[e] = lds128(sb + SHK + (e < 4 ? cA * 8 + e * 16 : (256 + cB) * 8));
#pragma unroll
        for (int r = 0; r < 11; r++) { LDS4(kk[r], ka + r * 128) kk[r][4] = lds32(kb + r * 128); }
#pragma unroll
        for (int r = 0; r < 8; r++) { LDS4(q[r], va + r * 128) q[r][4] = lds32(vb + r * 128); }
        __syncwarp();
        if (lane == 0) mbar_arrive(BAR(B_KVFREE));
        if (t == 0) TL(13);
      }
#pragma unroll
      for (int e = 0; e < 5; e++) {
        const uint32_t w0 = __byte_perm(sw[e].x, sw[e].z, 0x5410), w1 = __byte_perm(sw[e].x, sw[e].z, 0x7632);
        const uint32_t w2 = __byte_perm(sw[e].y, sw[e].w, 0x5410), w3 = __byte_perm(sw[e].y, sw[e].w, 0x7632);
#pragma unroll
        for (int r = 0; r < 8; r++) q[r][e] = bmul2(bfma2(kk[r + 3][e], w0, bfma2(kk[r + 2][e], w1, bfma2(kk[r + 1][e], w2, bmul2(kk[r][e], w3)))), q[r][e]);
        __nv_bfloat16* u0 = g_u + (320 * (b & 1) + (e < 4 ? cA + 2 * e : 256 + cB)) * S_ + (2040 - 32 * (b >> 1) - (e < 4 ? rA : rB));
        st_tagged(u0, __byte_perm(q[7][e], q[6][e], 0x5410), __byte_perm(q[5][e], q[4][e], 0x5410), __byte_perm(q[3][e], q[2][e], 0x5410), __byte_perm(q[1][e], q[0][e], 0x5410), tag);
        st_tagged(u0 + S_, __byte_perm(q[7][e], q[6][e], 0x7632), __byte_perm(q[5][e], q[4][e], 0x7632), __byte_perm(q[3][e], q[2][e], 0x7632), __byte_perm(q[1][e], q[0][e], 0x7632), tag);
      }
      __syncwarp();
      if (lane == 0) mbar_arrive(BAR(B_PUB2));
      if (t == 0) TL(12);
      uint4 uu[4];
      ld_tagged<1>(uu, g_u + 5 * b * S_ + t * 8, 0, tag);
      ld_tagged<3>(uu + 1, g_u + 5 * b * S_ + t * 8 + 1024, 1024, tag);
      if (t == 0) TL(8);
      mbar_wait(BAR(B_KVFREE), 0);
#pragma unroll
      for (int i = 0; i < 4; i++) sts128(sb + CONV + (i >> 1) * CB_BYTES + (i & 1) * 2048 + t * 16, uu[i].x, uu[i].y, uu[i].z, uu[i].w);
      fence_async_smem();
      __syncwarp();
      if (lane == 0) mbar_arrive(BAR(B_UFULL));
    }
    {
      const int x0 = 16 * w + b0 + 2 * c - 7;
      const uint32_t foff = sb + CONV + ((b0 & 1) ? CB_E + (x0 + 8) * 2 : CB_O + (x0 + 9) * 2);
      const uint32_t dump = sb + RED + w * RED_P + (31 - lane + 2 * w) * 16;
      uint32_t f[4][8];
      float d[128];
#define CONV_MMA(M, Sl)                                                                                      \
  {                                                                                                          \
    if ((M) == 0) wgmma_rs_n32_init(d + 16 * (Sl), f[0], hd + (uint64_t)(32 * (7 - (Sl))));                  \
    else wgmma_rs_n32(d + 16 * (Sl), f[((M) >> 1) & 3] + 4 * ((M) & 1), hd + (uint64_t)(32 * (7 - (Sl)) + 16 * (M)), 1); \
  }
#define CONV_FRAG(T, a) { conv_frag<2 * (T)>(f[(T) & 3], a); conv_frag<2 * (T) + 1>(f[(T) & 3] + 4, a); }
#define CONV_DUMP(Sl)                                                                                        \
  {                                                                                                          \
    uint32_t pk[4];                                                                                          \
    _Pragma("unroll") for (int g = 0; g < 4; g++) {                                                          \
      const int e = 16 * (Sl) + 4 * g, e2 = g < 3 ? e + 6 : (Sl) > 0 ? 16 * (Sl) - 14 : 0;                   \
      pk[g] = (g < 3 || (Sl) > 0) ? pack_bf16(d[e] + d[e2], d[e + 1] + d[e2 + 1]) : pack_bf16(d[e], d[e + 1]); \
    }                                                                                                        \
    stsm4t(dp + (Sl) * 512, pk[0], pk[1], pk[2], pk[3]);                                                     \
  }
#define CONV_SIG(Bk) { __syncwarp(); if (lane == 0) mbar_arrive(rf + 8 * (Bk)); }
#define CONV_ROW(T)                                                                                          \
  {                                                                                                          \
    if (T >= 2) wg_wait<1>();                                                                                \
    CONV_FRAG(T + 2, ab)                                                                                     \
    wg_fence();                                                                                              \
    CONV_MMA(2 * T, 7) CONV_MMA(2 * T, 6)                                                                    \
    if (T >= 2) CONV_DUMP(T >= 2 ? T - 2 : 0)                                                                \
    _Pragma("unroll") for (int bk = 5; bk >= T; bk--) CONV_MMA(2 * T, bk)                                    \
    if (T >= 2) CONV_SIG(T >= 2 ? T - 2 : 0)                                                                 \
    _Pragma("unroll") for (int bk = 7; bk >= T; bk--) CONV_MMA(2 * T + 1, bk)                                \
    wg_commit();                                                                                             \
  }
      mbar_wait(BAR(B_CFULL), 0);
      CONV_FRAG(0, foff) CONV_FRAG(1, foff)
      mbar_wait(BAR(B_UFULL), 0);
#pragma unroll 1
      for (int ch = 0; ch < 5; ch++) {
        const int buf = ch & 1;
        const uint32_t ab = foff + buf * CB_BYTES, abn = foff + (buf ^ 1) * CB_BYTES;
        const uint32_t dp = dump + buf * RED_BUF, rf = BAR(B_RFULL + 8 * buf);
        const uint64_t hd = mk_desc(sb + CONV + buf * CB_BYTES, 16, 128, 0);
        if (t == 0 && (TL_ALL || ch == 0)) TL(20 + 3 * ch);
        CONV_ROW(0)
        if (ch > 0) mbar_wait(ch == 1 ? BAR(B_G1DONE) : BAR(B_REMPTY + buf), ch >> 2);
        CONV_ROW(1) CONV_ROW(2)
        if (t == 0) mbar_arrive(BAR(B_TOK + 2 * ch));
        CONV_ROW(3) CONV_ROW(4) CONV_ROW(5)
        if (ch < 4) mbar_wait(BAR(B_CFULL + (buf ^ 1)), ((ch + 1) >> 1) & 1);
        wg_wait<1>();
        CONV_FRAG(0, abn)
        wg_fence();
        CONV_MMA(12, 7) CONV_MMA(12, 6) CONV_DUMP(4) CONV_MMA(13, 7) CONV_MMA(13, 6) CONV_SIG(4) CONV_MMA(14, 7) CONV_MMA(15, 7)
        wg_commit();
        if (lane == 0 || t == 1) mbar_arrive(lane ? BAR(B_TOK + 2 * ch + 1) : BAR(B_EOFREE + buf));
        wg_wait<1>();
        CONV_FRAG(1, abn)
        CONV_DUMP(5) CONV_SIG(5)
        wg_wait<0>();
        if (t == 0 && (TL_ALL || ch == 4)) TL(21 + 3 * ch);
        CONV_DUMP(6) CONV_DUMP(7)
        __syncwarp();
        if (lane < 3) mbar_arrive(lane == 2 ? BAR(B_CEMPTY + buf) : rf + 8 * (6 + lane));
      }
    }
    bar_sync(1, 128);
    if (elect_one()) {
      if (w == 0) mbar_expect(BAR(B_FINX), 20480);
      tma3d(sb + FIN_X + w * 5120, &P.x_t, 0, rb64 * 64 + w * 16, ns * 5, BAR(B_FINX));
    }
    {
      uint32_t xn[40], xb[40];
#pragma unroll
      for (int g = 0; g < 20; g++) xb[2 * g] = ldg32(P.b2 + ns * 160 + (g < 16 ? rot * 32 + 8 * g : (rot ? 8 * g - 128 : 8 * g)) + 2 * c);
      const float2 st0 = lds64f(sb + SSTAT + ((rb64 & 1) * 64 + 16 * w + b0) * 8);
      const float2 st1 = lds64f(sb + SSTAT + ((rb64 & 1) * 64 + 16 * w + b0 + 8) * 8);
      const uint32_t nm[2] = {pack_bf16(-st0.x, -st0.x), pack_bf16(-st1.x, -st1.x)}, rs[2] = {pack_bf16(st0.y, st0.y), pack_bf16(st1.y, st1.y)};
      const int mi = lane >> 3, li = lane & 7, xr = (mi & 1) * 8 + li;
      const uint32_t xa0 = sb + FIN_X + w * 5120 + xr * 64 + (((mi >> 1) ^ ((xr >> 1) & 3)) << 4);
      const uint32_t za0 = sb + FIN_Z + (8 * (mi >> 1) + li) * 128 + (((2 * w + (mi & 1)) ^ li) << 4);
      mbar_wait(BAR(B_FINX), 0);
#pragma unroll
      for (int p = 0; p < 10; p++) {
        uint32_t xv[4];
        ldsm4((xa0 ^ ((p & 1) << 5)) + TBLK(p) * 1024, xv);
#pragma unroll
        for (int e = 3; e >= 0; e--) {
          xn[4 * p + e] = bmul2(bfma2(xv[e], ONE2, nm[e & 1]), rs[e & 1]);
          xb[4 * p + e] = bfma2(xv[e], ONE2, xb[4 * p + (e & 2)]);
        }
      }
      {
        uint4 zz[10];
        ld_tagged<10>(zz, g_z + (ns * 160 + (t >> 3)) * S_ + rb64 * 64 + (t & 7) * 8, 16 * S_, tag);
        if (t == 0) TL(36);
        mbar_wait(BAR(B_RDONE), 0);
#pragma unroll
        for (int i = 0; i < 10; i++)
          sts128(sb + FIN_Z + (16 * i + (t >> 3)) * 128 + (((t & 7) ^ ((t >> 3) & 7)) << 4), zz[i].x, zz[i].y, zz[i].z, zz[i].w);
        bar_sync(1, 128);
      }
#pragma unroll
      for (int p = 0; p < 10; p++) {
        uint32_t zv[4];
        ldsm4t(za0 + (p & 1) * 2048 + TBLK(p) * 4096, zv);
        stsm4((xa0 ^ ((p & 1) << 5)) + TBLK(p) * 1024, bfma2(xn[4 * p], zv[0], xb[4 * p]), bfma2(xn[4 * p + 1], zv[1], xb[4 * p + 1]),
              bfma2(xn[4 * p + 2], zv[2], xb[4 * p + 2]), bfma2(xn[4 * p + 3], zv[3], xb[4 * p + 3]));
      }
      __syncwarp();
      if (lane == 0) mbar_arrive(BAR(B_BASE));
      if (t == 0) TL(37);
    }
  } else {
    bar_sync(0, 512);
    const int w = warp & 3, b0 = lane >> 2;
    const int mi = lane >> 3, li = lane & 7;
    {
      float acc[96];
#pragma unroll 1
      for (int kt = 0; kt < 10; kt++) {
        const int s = kt & 3;
        const uint32_t st = sb + s * ST1_BYTES;
        const uint64_t da = mk_desc(st + wg * 8192, 16, 1024, 1), db = mk_desc(st + ST1_B, 8192, 1024, 1);
        if (kt == PAUSE1 || kt == PAUSE2) {
          if (lane == 0) mbar_arrive(BAR(kt == PAUSE1 ? B_G1P1 : B_G1MAIN));
          mbar_wait(BAR(kt == PAUSE1 ? B_PUB1 : B_KVFREE), 0);
        }
        mbar_wait(BAR(B_FULL1 + s), (kt >> 2) & 1);
        if (tid == 0) TL(64 + kt);
        wg_fence();
#pragma unroll
        for (int kk = 0; kk < 4; kk++) wgmma_n192_bmn(acc, da + 2 * kk, db + 128 * kk, (kt | kk) != 0);
        wg_commit();
        if (kt > 0) { wg_wait<1>(); if (lane == 0) mbar_arrive(BAR(B_EMPTY1 + ((kt - 1) & 3))); }
      }
      if (PAUSE2 >= 10 && lane == 0) mbar_arrive(BAR(B_G1MAIN));
      if (tid == 0) TL(41);
      mbar_wait(BAR(B_AUG), 0);
      wg_fence();
      wgmma_n192_bk(acc, mk_desc(sb + AUG_A + wg * 2048, 128, 256, 0), mk_desc(sb + AUG_B, 128, 256, 0), 1);
      wg_commit();
      const float hr0 = 0.5f * lds64f(sb + SSTAT + (wg * 64 + 16 * w + b0) * 8).y;
      const float hr1 = 0.5f * lds64f(sb + SSTAT + (wg * 64 + 16 * w + b0 + 8) * 8).y;
      wg_wait<0>();
      if (lane == 0) mbar_arrive(BAR(B_G1DONE));
      if (tid == 0) TL(42);
      uint32_t hs = sb + HST + wg * 3 * 8192 + (16 * w + (mi & 1) * 8 + li) * 128 + (((mi >> 1) ^ li) << 4);
#pragma unroll 1
      for (int ch = 0; ch < 3; ch++) {
        uint32_t o[16];
#pragma unroll
        for (int g = 0; g < 8; g++) {
          o[2 * g] = pack_bf16(gelu_scaled(acc[4 * g], hr0), gelu_scaled(acc[4 * g + 1], hr0));
          o[2 * g + 1] = pack_bf16(gelu_scaled(acc[4 * g + 2], hr1), gelu_scaled(acc[4 * g + 3], hr1));
        }
        mbar_wait(BAR(B_G1DONE), 0);
#pragma unroll
        for (int p = 0; p < 4; p++) stsm4(hs ^ (p << 5), o[4 * p], o[4 * p + 1], o[4 * p + 2], o[4 * p + 3]);
        fence_async_smem();
        __syncwarp();
        if (lane == 0) mbar_arrive(BAR(B_HCH + wg * 3 + ch));
        if (tid == 0) TL(43 + ch);
        hs += 8192;
#pragma unroll
        for (int i = 0; i < 64; i++) acc[i] = acc[i + 32];
      }
    }
    if (wg == 1) {
      const uint32_t tag = tag_bits(read_epoch());
#pragma unroll 1
      for (int i = w; i < 40; i += 4) {
        const int ch = i >> 3, blk = i & 7, buf = ch & 1;
        const uint32_t ra = sb + RED + buf * RED_BUF + (32 * blk + lane) * 16;
        mbar_wait(BAR(B_RFULL + 8 * buf + blk), (ch >> 1) & 1);
        uint4 p[4];
#pragma unroll
        for (int ww = 0; ww < 4; ww++) p[ww] = lds128(ra + ww * RED_P);
        __syncwarp();
        if (lane == 0) mbar_arrive(BAR(B_REMPTY + buf));
        if (blk == 0) {
#pragma unroll
          for (int ww = 1; ww < 4; ww++) if (lane < 2 * ww) p[ww] = make_uint4(0, 0, 0, 0);
        }
        uint32_t o[4];
#pragma unroll
        for (int e = 0; e < 4; e++) {
          const uint32_t a0 = (&p[0].x)[e], a1 = (&p[1].x)[e], a2 = (&p[2].x)[e], a3 = (&p[3].x)[e];
          o[e] = pack_bf16((bf_lo(a0) + bf_lo(a1)) + (bf_lo(a2) + bf_lo(a3)), (bf_hi(a0) + bf_hi(a1)) + (bf_hi(a2) + bf_hi(a3)));
        }
        st_tagged(g_z + (5 * b + ch) * S_ + (32 * blk + lane) * 8, o[0], o[1], o[2], o[3], tag);
        if (lane == 0 && blk == 7 && (TL_ALL || ch == 4)) TL(22 + 3 * ch);
      }
      __syncwarp();
      if (lane == 0) mbar_arrive(BAR(B_RDONE));
    } else {
      float acc[80];
      const uint32_t lo0 = (sb & 0x3FFFF) >> 4;
      const uint32_t own = lo0 + ((HST + (rb64 & 1) * 3 * 8192) >> 4), oth = lo0 + ((HST + ((rb64 & 1) ^ 1) * 3 * 8192) >> 4);
#define G2_DESC(lo, lbo) (((uint64_t)0x40000040u << 32) | (uint64_t)((lo) | ((lbo) << 12)))
#define G2_TILE(A, B, S)                                                                                     \
  {                                                                                                          \
    const bool more = (S) > 0 || r > 0;                                                                      \
    if ((S) < 3 && r == 0) mbar_wait(BAR(B_HCH + (S)) + (rb64 & 1) * 24, 0);                                 \
    const int tk = (5 * r + (S) - 3) * G2_TMUL / G2_TDIV + G2_TOFF;                                          \
    const bool gated = 5 * r + (S) >= 3 && tk < 10;                                                          \
    const bool rdy = !gated && __all_sync(~0u, mbar_try_nb(BAR(B_FULL2 + (S)), r & 1));                      \
    if (!rdy) {                                                                                              \
      wg_wait<0>();                                                                                          \
      if (more && lane == 0) mbar_arrive(BAR(B_EMPTY2 + ((S) + 4) % 5));                                     \
      mbar_wait(BAR(B_FULL2 + (S)), r & 1);                                                                  \
      if (gated) mbar_wait(BAR(B_TOK + tk), 0);                                                              \
    }                                                                                                        \
    wg_fence();                                                                                              \
    _Pragma("unroll") for (int kk = 0; kk < 4; kk++)                                                         \
      wgmma_n160_bmn(acc, G2_DESC((A) + 2 * kk, 16), G2_DESC((B) + 128 * kk, 8192), more || kk != 0);        \
    wg_commit();                                                                                             \
    if (rdy) { wg_wait<1>(); if (more && lane == 0) mbar_arrive(BAR(B_EMPTY2 + ((S) + 4) % 5)); }            \
  }
#define G2_B(S) (lz + ((R2B + (S) * ST2B_BYTES) >> 4))
#pragma unroll 1
      for (int r = 0;; r++) {
        uint32_t z;
        asm volatile("mov.u32 %0, 0;\n" : "=r"(z));
        z = __shfl_sync(~0u, z, 0);
        const uint32_t lz = lo0 + z, a3 = (r == 0 ? own : oth) + z;
        if (tid == 0) TL(80 + 5 * r);
        G2_TILE(a3, G2_B(0), 0) G2_TILE(a3 + 512, G2_B(1), 1) G2_TILE(a3 + 1024, G2_B(2), 2)
        G2_TILE(lz + (R2A >> 4), G2_B(3), 3)
        if (r == 4) break;
        G2_TILE(lz + ((R2A + 8192) >> 4), own + z, 4)
      }
      if (tid == 0) TL(104);
      uint32_t base[40];
      const int xr = (mi & 1) * 8 + li;
      const uint32_t xa0 = sb + FIN_X + w * 5120 + xr * 64 + (((mi >> 1) ^ ((xr >> 1) & 3)) << 4);
      mbar_wait(BAR(B_BASE), 0);
#pragma unroll
      for (int p = 0; p < 10; p++) ldsm4((xa0 ^ ((p & 1) << 5)) + TBLK(p) * 1024, base + 4 * p);
      wg_wait<0>();
      if (tid == 0) TL(49);
#pragma unroll
      for (int p = 0; p < 10; p++) {
        uint32_t o[4];
#pragma unroll
        for (int e = 0; e < 4; e++) o[e] = bfma2(pack_bf16(acc[8 * p + 2 * e], acc[8 * p + 2 * e + 1]), ONE2, base[4 * p + e]);
        stsm4((xa0 ^ ((p & 1) << 5)) + TBLK(p) * 1024, o[0], o[1], o[2], o[3]);
      }
      fence_async_smem();
      __syncwarp();
      if (elect_one()) {
        tma3d_store(&P.out, 0, rb64 * 64 + w * 16, ns * 5, sb + FIN_X + w * 5120);
        bulk_commit();
        if (w == 0) flag_arrive_relaxed(FL_DONE);
        bulk_wait_read<0>();
        if (w == 0) TL(50);
      }
    }
  }
}

typedef CUresult (*EncodeFn)(CUtensorMap*, CUtensorMapDataType, cuuint32_t, void*, const cuuint64_t*, const cuuint64_t*,
                             const cuuint32_t*, const cuuint32_t*, CUtensorMapInterleave, CUtensorMapSwizzle,
                             CUtensorMapL2promotion, CUtensorMapFloatOOBfill);

void enc2d(EncodeFn f, CUtensorMap* m, const void* p, uint64_t d0, uint64_t d1, uint32_t b0, uint32_t b1, CUtensorMapSwizzle sw) {
  cuuint64_t dims[2] = {d0, d1}, str[1] = {d0 * 2};
  cuuint32_t box[2] = {b0, b1}, es[2] = {1, 1};
  f(m, CU_TENSOR_MAP_DATA_TYPE_BFLOAT16, 2, const_cast<void*>(p), dims, str, box, es, CU_TENSOR_MAP_INTERLEAVE_NONE, sw,
    CU_TENSOR_MAP_L2_PROMOTION_L2_128B, CU_TENSOR_MAP_FLOAT_OOB_FILL_NONE);
}
void enc3d(EncodeFn f, CUtensorMap* m, const void* p, uint64_t rows, uint64_t cols, uint32_t blk, uint32_t brows, uint32_t bblk,
           CUtensorMapSwizzle sw) {
  cuuint64_t dims[3] = {blk, rows, cols / blk}, str[2] = {cols * 2, (uint64_t)blk * 2};
  cuuint32_t box[3] = {blk, brows, bblk}, es[3] = {1, 1, 1};
  f(m, CU_TENSOR_MAP_DATA_TYPE_BFLOAT16, 3, const_cast<void*>(p), dims, str, box, es, CU_TENSOR_MAP_INTERLEAVE_NONE, sw,
    CU_TENSOR_MAP_L2_PROMOTION_L2_128B, CU_TENSOR_MAP_FLOAT_OOB_FILL_NONE);
}

}

extern "C" void kernel_launch(void* const* d_in, const int* in_sizes, int n_in, void* d_out, int out_size) {
  (void)in_sizes; (void)n_in; (void)out_size;
  static EncodeFn enc = nullptr;
  static void *ph = nullptr;
  if (!enc) {
    void* fn = nullptr;
    cudaDriverEntryPointQueryResult qr;
    cudaGetDriverEntryPoint("cuTensorMapEncodeTiled", &fn, cudaEnableDefault, &qr);
    enc = (EncodeFn)fn;
    cudaGetSymbolAddress(&ph, g_h);
    cudaFuncSetAttribute(fused_kernel, cudaFuncAttributeMaxDynamicSharedMemorySize, SMEM_BYTES);
  }
  typedef const __nv_bfloat16* bp;
  Params P;
  P.x = (bp)d_in[0]; P.k = (bp)d_in[1]; P.v = (bp)d_in[2]; P.shift_k = (bp)d_in[3]; P.ssm_k = (bp)d_in[4]; P.ssm_D = (bp)d_in[5];
  P.w1p = (bp)d_in[7]; P.b1 = (bp)d_in[8]; P.w2p = (bp)d_in[9]; P.b2 = (bp)d_in[10];
  enc2d(enc, &P.x_a, P.x, D_, S_, 64, 128, CU_TENSOR_MAP_SWIZZLE_128B);
  enc3d(enc, &P.w1, P.w1p, D_, F_, 64, 64, 3, CU_TENSOR_MAP_SWIZZLE_128B);
  enc3d(enc, &P.kt, P.k, S_, D_, 64, 35, 1, CU_TENSOR_MAP_SWIZZLE_NONE);
  enc3d(enc, &P.vt, P.v, S_, D_, 64, 32, 1, CU_TENSOR_MAP_SWIZZLE_NONE);
  enc2d(enc, &P.h, ph, F_, S_, 64, 64, CU_TENSOR_MAP_SWIZZLE_128B);
  enc3d(enc, &P.w2, P.w2p, F_, D_, 64, 64, 2, CU_TENSOR_MAP_SWIZZLE_128B);
  enc2d(enc, &P.w2h, P.w2p, D_, F_, 32, 64, CU_TENSOR_MAP_SWIZZLE_128B);
  enc3d(enc, &P.x_t, P.x, S_, D_, 32, 16, 5, CU_TENSOR_MAP_SWIZZLE_64B);
  enc3d(enc, &P.out, d_out, S_, D_, 32, 16, 5, CU_TENSOR_MAP_SWIZZLE_64B);
  fused_kernel<<<NCTA, 512, SMEM_BYTES, cudaStreamPerThread>>>(P);
}
```

```cpp
#include <cuda.h>
#include <cuda_runtime.h>
#include <cuda_bf16.h>
#include <stdint.h>

namespace {

constexpr int S_ = 2048, D_ = 640, F_ = 1536;
constexpr int NCTA = 128;
#define GELU_UN 1
constexpr int GELU_UNROLL = GELU_UN;
#define PFX_T 700
#define PFW_T 1200
#define XSH_T 600
#define W1_T 2500
#define KV_T 3000
#define KV_STEP 330
#define PF_T 7500
#define PF_STEP 350
#define AUG_T 300
#define LL_SLEEP 100
#define G2_TOFF 0
#define G2_TMUL 3
#define G2_TDIV 4
#define H_AFTER_U 9
#define PAUSE1 99
#define PAUSE2 7
#define B_AFTER_U 1
#define U_SENT 1
#define U_AFTER_AUG 0
#define W2_EARLY 1
#define UH_AFTER 0
#define UH_DELAY 0
#define ZH_NS 0
#define AUG2_T 6500
#define GELU_PACKED 0
#define TL_ROWS 0
#define UH_WAIT 1
#define TM_T 2500
#define FW 1
#define FW2 0
#define G1_GATE 0
#define CONV_GATE 0
#define UH_D 1500
#define PAUSE_FULL 0
#define SEP_U 1
#define ZH_D 1500
#define W23 0
#define U_LATE 99
#define ADAPT 0
#define KV_GATE 1
#define TL_ALL 1

__device__ __align__(1024) __nv_bfloat16 g_h[S_ * F_];
__device__ __align__(1024) __nv_bfloat16 g_u[D_ * S_];
__device__ __align__(1024) __nv_bfloat16 g_z[D_ * S_];
__device__ __align__(1024) uint4 g_pa[S_];
__device__ __align__(1024) uint4 g_pb[4 * F_ / 2];
constexpr int FL_STRIDE = 32;
constexpr int FL_DONE = 0, FL_U = 1, FL_UH = 2, FL_ZH = 3, FL_H = 7, FL_COUNT = 7 + 32;
__device__ __align__(1024) unsigned g_flags[FL_COUNT * FL_STRIDE];
#define TL(i) do { } while (0)

constexpr int ST1_BYTES = 40960, ST1_B = 16384;
constexpr int HST = 0;
constexpr int R2A = 49152, R2B = 65536, ST2B_BYTES = 24576;
constexpr int CONV = 163840;
constexpr int CB_BYTES = 12800, CB_E = 4480, CB_O = 8640;
constexpr int RED = CONV + 2 * CB_BYTES, RED_P = 4224, RED_BUF = 4 * RED_P;
constexpr int AUG_B = RED + RED_BUF + 512, AUG_A = AUG_B + 6144, CS_TMP = AUG_A + 4096;
constexpr int KV_K = CONV, KV_V = CONV + 22400, XSH = AUG_B;
constexpr int UST = RED, UST4 = CONV + CB_BYTES;
constexpr int U3 = RED + 2 * RED_BUF;
constexpr int FIN_X = RED + RED_BUF, FIN_Z = CONV;
constexpr int SSTAT = XSH + 20480 + 288;
constexpr int SHK = SSTAT + 1024;
constexpr int SB2 = SHK + 2560;
constexpr int BARS = SB2 + 320;
constexpr int SMEM_BYTES = BARS + 720;
static_assert(SMEM_BYTES <= 232448 && SSTAT >= RED + 2 * RED_BUF && KV_V + 20480 <= AUG_B && CS_TMP + 3840 <= SSTAT, "smem");
static_assert(U3 + 4384 <= SSTAT && FIN_X + 20480 <= SSTAT && FIN_X % 512 == 0, "late");
static_assert(FIN_Z % 1024 == 0 && CONV % 1024 == 0 && RED % 128 == 0, "align");
constexpr int SMEM_ALLOC = SMEM_BYTES;
static_assert(SMEM_ALLOC <= 232448, "smem");
enum { B_FULL1 = 0, B_FULL2 = 4, B_PUB2 = 9, B_ZRDY = 10, B_HRD = 11, B_FINX = 12, B_XSH = 13, B_KV = 14, B_HRDY = 15, B_H0 = 17,
       B_TOK = 20,
       B_AUG = 30, B_CFULL = 31,
       B_HCH = 40, B_CEMPTY = 46, B_RFULL = 48, B_RDONE = 64, B_XFREE = 65, B_KVFREE = 66, B_UFULL = 67, B_EMPTY2 = 68,
       B_EOFREE = 73, B_PUB1 = 75,
       B_EMPTY1 = 80, B_G1DONE = 84, B_G1MAIN = 85, B_REMPTY = 86, B_BASE = 88, B_COUNT = 90 };

__device__ __forceinline__ uint32_t smem_u32(const void* p) { return (uint32_t)__cvta_generic_to_shared(p); }
__device__ __forceinline__ uint64_t mk_desc(uint32_t addr, uint32_t lbo, uint32_t sbo, uint32_t swz) {
  return (uint64_t)((addr & 0x3FFFF) >> 4) | ((uint64_t)(lbo >> 4) << 16) | ((uint64_t)(sbo >> 4) << 32) | ((uint64_t)swz << 62);
}
__device__ __forceinline__ void wg_fence() { asm volatile("wgmma.fence.sync.aligned;\n" ::: "memory"); }
__device__ __forceinline__ void wg_commit() { asm volatile("wgmma.commit_group.sync.aligned;\n" ::: "memory"); }
template <int N> __device__ __forceinline__ void wg_wait() { asm volatile("wgmma.wait_group.sync.aligned %0;\n" ::"n"(N) : "memory"); }
__device__ __forceinline__ void mbar_init(uint32_t b, int c) { asm volatile("mbarrier.init.shared::cta.b64 [%0], %1;\n" ::"r"(b), "r"(c) : "memory"); }
__device__ __forceinline__ void mbar_expect(uint32_t b, int bytes) {
  asm volatile("mbarrier.arrive.expect_tx.shared::cta.b64 _, [%0], %1;\n" ::"r"(b), "r"(bytes) : "memory");
}
__device__ __forceinline__ void mbar_arrive(uint32_t b) { asm volatile("mbarrier.arrive.shared::cta.b64 _, [%0];\n" ::"r"(b) : "memory"); }
__device__ __forceinline__ bool mbar_try(uint32_t b, int par) {
  uint32_t ok;
  asm volatile("{\n.reg .pred p;\nmbarrier.try_wait.parity.shared::cta.b64 p, [%1], %2;\nselp.u32 %0, 1, 0, p;\n}\n"
               : "=r"(ok) : "r"(b), "r"(par) : "memory");
  return ok;
}
__device__ __forceinline__ bool mbar_try_nb(uint32_t b, int par) {
  uint32_t ok;
  asm volatile("{\n.reg .pred p;\nmbarrier.test_wait.parity.shared::cta.b64 p, [%1], %2;\nselp.u32 %0, 1, 0, p;\n}\n"
               : "=r"(ok) : "r"(b), "r"(par) : "memory");
  return ok;
}
__device__ __forceinline__ void mbar_wait(uint32_t b, int par) {
  asm volatile(
      "{\n.reg .pred p;\n.reg .u32 n;\nmov.u32 n, 0;\n"
      "WAIT_LOOP:\n"
      "mbarrier.try_wait.parity.shared::cta.b64 p, [%0], %1;\n"
      "@p bra WAIT_DONE;\n"
      "add.u32 n, n, 1;\n"
      "setp.lt.u32 p, n, 4096;\n"
      "@p bra WAIT_LOOP;\n"
      "WAIT_DONE:\n}\n" ::"r"(b), "r"(par) : "memory");
}
__device__ __forceinline__ bool elect_one() {
  uint32_t p;
  asm volatile("{\n.reg .pred q;\nelect.sync _|q, 0xffffffff;\nselp.u32 %0, 1, 0, q;\n}\n" : "=r"(p));
  return p;
}
__device__ __forceinline__ void fence_async() { asm volatile("fence.proxy.async.global;\n" ::: "memory"); }
__device__ __forceinline__ void fence_async_smem() { asm volatile("fence.proxy.async.shared::cta;\n" ::: "memory"); }
__device__ __forceinline__ void bar_sync(int id, int n) { asm volatile("bar.sync %0, %1;\n" ::"r"(id), "r"(n) : "memory"); }
__device__ __forceinline__ bool wg_any(bool p, int id) {
  uint32_t r;
  asm volatile("{\n.reg .pred a, b;\nsetp.ne.u32 a, %1, 0;\nbar.red.or.pred b, %2, 128, a;\nselp.u32 %0, 1, 0, b;\n}\n" : "=r"(r) : "r"((uint32_t)p), "r"(id) : "memory");
  return r;
}
__device__ __forceinline__ void tma2d(uint32_t dst, const CUtensorMap* m, int c0, int c1, uint32_t bar) {
  asm volatile("cp.async.bulk.tensor.2d.shared::cluster.global.mbarrier::complete_tx::bytes [%0], [%1, {%3, %4}], [%2];\n"
               ::"r"(dst), "l"(m), "r"(bar), "r"(c0), "r"(c1) : "memory");
}
__device__ __forceinline__ void tma3d(uint32_t dst, const CUtensorMap* m, int c0, int c1, int c2, uint32_t bar) {
  asm volatile("cp.async.bulk.tensor.3d.shared::cluster.global.mbarrier::complete_tx::bytes [%0], [%1, {%3, %4, %5}], [%2];\n"
               ::"r"(dst), "l"(m), "r"(bar), "r"(c0), "r"(c1), "r"(c2) : "memory");
}
__device__ __forceinline__ void tma2d_store(const CUtensorMap* m, int c0, int c1, uint32_t src) {
  asm volatile("cp.async.bulk.tensor.2d.global.shared::cta.bulk_group [%0, {%2, %3}], [%1];\n"
               ::"l"(m), "r"(src), "r"(c0), "r"(c1) : "memory");
}
__device__ __forceinline__ void tma3d_store(const CUtensorMap* m, int c0, int c1, int c2, uint32_t src) {
  asm volatile("cp.async.bulk.tensor.3d.global.shared::cta.bulk_group [%0, {%2, %3, %4}], [%1];\n"
               ::"l"(m), "r"(src), "r"(c0), "r"(c1), "r"(c2) : "memory");
}
__device__ __forceinline__ void tma4d_store(const CUtensorMap* m, int c0, int c3, uint32_t src) {
  asm volatile("cp.async.bulk.tensor.4d.global.shared::cta.bulk_group [%0, {%2, 0, 0, %3}], [%1];\n"
               ::"l"(m), "r"(src), "r"(c0), "r"(c3) : "memory");
}
__device__ __forceinline__ void bulk_g2s(uint32_t dst, const void* src, int bytes, uint32_t bar) {
  asm volatile("cp.async.bulk.shared::cluster.global.mbarrier::complete_tx::bytes [%0], [%1], %2, [%3];\n"
               ::"r"(dst), "l"(src), "r"(bytes), "r"(bar) : "memory");
}
__device__ __forceinline__ void bulk_s2g(void* dst, uint32_t src, int bytes) {
  asm volatile("cp.async.bulk.global.shared::cta.bulk_group [%0], [%1], %2;\n" ::"l"(dst), "r"(src), "r"(bytes) : "memory");
}
__device__ __forceinline__ void bulk_commit() { asm volatile("cp.async.bulk.commit_group;\n" ::: "memory"); }
template <int N> __device__ __forceinline__ void bulk_wait() { asm volatile("cp.async.bulk.wait_group %0;\n" ::"n"(N) : "memory"); }
template <int N> __device__ __forceinline__ void bulk_wait_read() { asm volatile("cp.async.bulk.wait_group.read %0;\n" ::"n"(N) : "memory"); }
__device__ __forceinline__ void l2_prefetch(const void* p, int bytes) {
  asm volatile("cp.async.bulk.prefetch.L2.global [%0], %1;\n" ::"l"(p), "r"(bytes) : "memory");
}
__device__ __forceinline__ void wait_until(unsigned t) {
  while ((int)(clock() - t) < 0) __nanosleep(64);
}
__device__ __forceinline__ void prefetch_l2(const void* p) { asm volatile("prefetch.global.L2 [%0];\n" ::"l"(p) : "memory"); }
__device__ __forceinline__ void tmap_prefetch(const CUtensorMap* m) { asm volatile("prefetch.tensormap [%0];\n" ::"l"(m) : "memory"); }
__device__ __forceinline__ void flag_arrive(int idx) {
  asm volatile("red.release.gpu.global.add.u32 [%0], 1;\n" ::"l"(g_flags + idx * FL_STRIDE) : "memory");
}
__device__ __forceinline__ unsigned flag_ld(int idx) {
  unsigned v;
  asm volatile("ld.acquire.gpu.global.u32 %0, [%1];\n" : "=r"(v) : "l"(g_flags + idx * FL_STRIDE) : "memory");
  return v;
}
__device__ __forceinline__ unsigned flag_ld_relaxed(int idx) {
  unsigned v;
  asm volatile("ld.relaxed.gpu.global.u32 %0, [%1];\n" : "=r"(v) : "l"(g_flags + idx * FL_STRIDE) : "memory");
  return v;
}
__device__ __forceinline__ void flag_arrive_relaxed(int idx) {
  asm volatile("red.relaxed.gpu.global.add.u32 [%0], 1;\n" ::"l"(g_flags + idx * FL_STRIDE) : "memory");
}
__device__ __forceinline__ void flag_wait(int idx, unsigned target) {
#pragma unroll 1
  for (int it = 0; it < (1 << 16); it++) { if ((int)(flag_ld_relaxed(idx) - target) >= 0) break; __nanosleep(40); }
  (void)flag_ld(idx);
}
__device__ __forceinline__ void flag_wait_relaxed(int idx, unsigned target) {
#pragma unroll 1
  for (int it = 0; it < (1 << 16); it++) { if ((int)(flag_ld_relaxed(idx) - target) >= 0) break; __nanosleep(40); }
}
__device__ __forceinline__ unsigned read_epoch() {
  unsigned v;
  asm volatile("ld.relaxed.gpu.global.u32 %0, [%1];\n" : "=r"(v) : "l"(g_flags + FL_DONE * FL_STRIDE) : "memory");
  return (v >> 7) + 1;
}
__device__ __forceinline__ uint32_t lds32(uint32_t a) { uint32_t r; asm volatile("ld.shared.u32 %0, [%1];\n" : "=r"(r) : "r"(a) : "memory"); return r; }
__device__ __forceinline__ float2 lds64f(uint32_t a) {
  float2 r; asm volatile("ld.shared.v2.f32 {%0, %1}, [%2];\n" : "=f"(r.x), "=f"(r.y) : "r"(a) : "memory"); return r;
}
__device__ __forceinline__ uint4 lds128(uint32_t a) {
  uint4 r; asm volatile("ld.shared.v4.u32 {%0, %1, %2, %3}, [%4];\n" : "=r"(r.x), "=r"(r.y), "=r"(r.z), "=r"(r.w) : "r"(a) : "memory"); return r;
}
__device__ __forceinline__ void sts64f(uint32_t a, float x, float y) { asm volatile("st.shared.v2.f32 [%0], {%1, %2};\n" ::"r"(a), "f"(x), "f"(y) : "memory"); }
__device__ __forceinline__ void sts32f(uint32_t a, float x) { asm volatile("st.shared.f32 [%0], %1;\n" ::"r"(a), "f"(x) : "memory"); }
__device__ __forceinline__ void sts128(uint32_t a, uint32_t x, uint32_t y, uint32_t z, uint32_t w) {
  asm volatile("st.shared.v4.u32 [%0], {%1, %2, %3, %4};\n" ::"r"(a), "r"(x), "r"(y), "r"(z), "r"(w) : "memory");
}
__device__ __forceinline__ void stsm4(uint32_t a, uint32_t r0, uint32_t r1, uint32_t r2, uint32_t r3) {
  asm volatile("stmatrix.sync.aligned.m8n8.x4.shared.b16 [%0], {%1, %2, %3, %4};\n" ::"r"(a), "r"(r0), "r"(r1), "r"(r2), "r"(r3) : "memory");
}
__device__ __forceinline__ void stsm4t(uint32_t a, uint32_t r0, uint32_t r1, uint32_t r2, uint32_t r3) {
  asm volatile("stmatrix.sync.aligned.m8n8.x4.trans.shared.b16 [%0], {%1, %2, %3, %4};\n" ::"r"(a), "r"(r0), "r"(r1), "r"(r2), "r"(r3) : "memory");
}
__device__ __forceinline__ void ldsm4(uint32_t a, uint32_t* r) {
  asm volatile("ldmatrix.sync.aligned.m8n8.x4.shared.b16 {%0, %1, %2, %3}, [%4];\n"
               : "=r"(r[0]), "=r"(r[1]), "=r"(r[2]), "=r"(r[3]) : "r"(a) : "memory");
}
__device__ __forceinline__ void ldsm4t(uint32_t a, uint32_t* r) {
  asm volatile("ldmatrix.sync.aligned.m8n8.x4.trans.shared.b16 {%0, %1, %2, %3}, [%4];\n"
               : "=r"(r[0]), "=r"(r[1]), "=r"(r[2]), "=r"(r[3]) : "r"(a) : "memory");
}
__device__ __forceinline__ uint32_t pack_bf16(float lo, float hi) {
  uint32_t r; asm("cvt.rn.bf16x2.f32 %0, %1, %2;\n" : "=r"(r) : "f"(hi), "f"(lo)); return r;
}
__device__ __forceinline__ float bf_lo(uint32_t v) { return __uint_as_float(v << 16); }
__device__ __forceinline__ float bf_hi(uint32_t v) { return __uint_as_float(v & 0xffff0000u); }
__device__ __forceinline__ float bf_round(float x) { return bf_lo(pack_bf16(x, 0.f)); }
__device__ __forceinline__ uint32_t bmul2(uint32_t a, uint32_t b) { uint32_t r; asm("mul.rn.bf16x2 %0, %1, %2;\n" : "=r"(r) : "r"(a), "r"(b)); return r; }
__device__ __forceinline__ uint32_t bfma2(uint32_t a, uint32_t b, uint32_t c) {
  uint32_t r; asm("fma.rn.bf16x2 %0, %1, %2, %3;\n" : "=r"(r) : "r"(a), "r"(b), "r"(c)); return r;
}
__device__ __forceinline__ float tanh_fast(float x) { float r; asm("tanh.approx.f32 %0, %1;\n" : "=f"(r) : "f"(x)); return r; }
__device__ __forceinline__ uint4 ldg128(const void* p) {
  uint4 r; asm volatile("ld.global.nc.L1::no_allocate.v4.u32 {%0, %1, %2, %3}, [%4];\n" : "=r"(r.x), "=r"(r.y), "=r"(r.z), "=r"(r.w) : "l"(p)); return r;
}
__device__ __forceinline__ uint32_t ldg32(const void* p) {
  uint32_t r; asm volatile("ld.global.nc.L1::no_allocate.u32 %0, [%1];\n" : "=r"(r) : "l"(p)); return r;
}
__device__ __forceinline__ uint4 ld_pkt(const uint4* p) {
  uint4 r;
  asm volatile("{\n.reg .b128 t;\n.reg .b64 a, b;\nld.relaxed.gpu.global.b128 t, [%4];\nmov.b128 {a, b}, t;\nmov.b64 {%0, %1}, a;\nmov.b64 {%2, %3}, b;\n}\n"
               : "=r"(r.x), "=r"(r.y), "=r"(r.z), "=r"(r.w) : "l"(p) : "memory");
  return r;
}
__device__ __forceinline__ void st_pkt(uint4* p, uint32_t x, uint32_t y, uint32_t z, uint32_t w) {
  asm volatile("{\n.reg .b128 t;\n.reg .b64 a, b;\nmov.b64 a, {%1, %2};\nmov.b64 b, {%3, %4};\nmov.b128 t, {a, b};\nst.relaxed.gpu.global.b128 [%0], t;\n}\n"
               ::"l"(p), "r"(x), "r"(y), "r"(z), "r"(w) : "memory");
}
__device__ __forceinline__ uint32_t tag_bits(unsigned ep) { return (ep & 1u) | ((ep & 2u) << 15); }
__device__ __forceinline__ void st_tagged(void* p, uint32_t x, uint32_t y, uint32_t z, uint32_t w, uint32_t tag) {
  st_pkt(reinterpret_cast<uint4*>(p), (x & ~0x00010001u) | tag, y, z, w);
}
template <int N0, int N1, bool FRESH = true>
__device__ __forceinline__ void ld_tagged(uint4* r, const __nv_bfloat16* p, int s0, int s1, uint32_t tag) {
  constexpr int N = N0 * N1;
#pragma unroll
  for (int i = 0; i < N; i++) if (FRESH) r[i].x = ~tag;
#pragma unroll 1
  for (int it = 0; it < (1 << 12); it++) {
    uint32_t bad = 0;
#pragma unroll
    for (int i = 0; i < N; i++)
      if ((r[i].x ^ tag) & 0x00010001u) r[i] = ld_pkt(reinterpret_cast<const uint4*>(p + (i % N0) * s0 + (i / N0) * s1));
#pragma unroll
    for (int i = 0; i < N; i++) bad |= r[i].x ^ tag;
    if (!__any_sync(~0u, bad & 0x00010001u)) break;
    __nanosleep(LL_SLEEP);
  }
}
__device__ __forceinline__ float2 ldcg64f(const void* p) {
  float2 r; asm volatile("ld.global.cg.v2.f32 {%0, %1}, [%2];\n" : "=f"(r.x), "=f"(r.y) : "l"(p) : "memory"); return r;
}
__device__ __forceinline__ void stg128(void* p, uint32_t x, uint32_t y, uint32_t z, uint32_t w) {
  asm volatile("st.global.v4.u32 [%0], {%1, %2, %3, %4};\n" ::"l"(p), "r"(x), "r"(y), "r"(z), "r"(w) : "memory");
}

__device__ __forceinline__ void wgmma_rs_n32_init(float* d, const uint32_t* a, uint64_t db) {
  asm volatile("{\n.reg .pred p;\nsetp.ne.b32 p, 0, 0;\n"
    "wgmma.mma_async.sync.aligned.m64n32k16.f32.bf16.bf16 {%0, %1, %2, %3, %4, %5, %6, %7, %8, %9, %10, %11, %12, %13, %14, %15}, {%16, %17, %18, %19}, %20, p, 1, 1, 0;\n}\n"
    : "=f"(d[0]), "=f"(d[1]), "=f"(d[2]), "=f"(d[3]), "=f"(d[4]), "=f"(d[5]), "=f"(d[6]), "=f"(d[7]), "=f"(d[8]), "=f"(d[9]), "=f"(d[10]), "=f"(d[11]), "=f"(d[12]), "=f"(d[13]), "=f"(d[14]), "=f"(d[15])
    : "r"(a[0]), "r"(a[1]), "r"(a[2]), "r"(a[3]), "l"(db));
}
__device__ __forceinline__ void wgmma_n192_bmn(float* d, uint64_t da, uint64_t db, int sc) {
  asm volatile("{\n.reg .pred p;\nsetp.ne.b32 p, %98, 0;\n"
    "wgmma.mma_async.sync.aligned.m64n192k16.f32.bf16.bf16 {%0, %1, %2, %3, %4, %5, %6, %7, %8, %9, %10, %11, %12, %13, %14, %15, %16, %17, %18, %19, %20, %21, %22, %23, %24, %25, %26, %27, %28, %29, %30, %31, %32, %33, %34, %35, %36, %37, %38, %39, %40, %41, %42, %43, %44, %45, %46, %47, %48, %49, %50, %51, %52, %53, %54, %55, %56, %57, %58, %59, %60, %61, %62, %63, %64, %65, %66, %67, %68, %69, %70, %71, %72, %73, %74, %75, %76, %77, %78, %79, %80, %81, %82, %83, %84, %85, %86, %87, %88, %89, %90, %91, %92, %93, %94, %95}, %96, %97, p, 1, 1, 0, 1;\n}\n"
    : "+f"(d[0]), "+f"(d[1]), "+f"(d[2]), "+f"(d[3]), "+f"(d[4]), "+f"(d[5]), "+f"(d[6]), "+f"(d[7]), "+f"(d[8]), "+f"(d[9]), "+f"(d[10]), "+f"(d[11]), "+f"(d[12]), "+f"(d[13]), "+f"(d[14]), "+f"(d[15]), "+f"(d[16]), "+f"(d[17]), "+f"(d[18]), "+f"(d[19]), "+f"(d[20]), "+f"(d[21]), "+f"(d[22]), "+f"(d[23]), "+f"(d[24]), "+f"(d[25]), "+f"(d[26]), "+f"(d[27]), "+f"(d[28]), "+f"(d[29]), "+f"(d[30]), "+f"(d[31]), "+f"(d[32]), "+f"(d[33]), "+f"(d[34]), "+f"(d[35]), "+f"(d[36]), "+f"(d[37]), "+f"(d[38]), "+f"(d[39]), "+f"(d[40]), "+f"(d[41]), "+f"(d[42]), "+f"(d[43]), "+f"(d[44]), "+f"(d[45]), "+f"(d[46]), "+f"(d[47]), "+f"(d[48]), "+f"(d[49]), "+f"(d[50]), "+f"(d[51]), "+f"(d[52]), "+f"(d[53]), "+f"(d[54]), "+f"(d[55]), "+f"(d[56]), "+f"(d[57]), "+f"(d[58]), "+f"(d[59]), "+f"(d[60]), "+f"(d[61]), "+f"(d[62]), "+f"(d[63]), "+f"(d[64]), "+f"(d[65]), "+f"(d[66]), "+f"(d[67]), "+f"(d[68]), "+f"(d[69]), "+f"(d[70]), "+f"(d[71]), "+f"(d[72]), "+f"(d[73]), "+f"(d[74]), "+f"(d[75]), "+f"(d[76]), "+f"(d[77]), "+f"(d[78]), "+f"(d[79]), "+f"(d[80]), "+f"(d[81]), "+f"(d[82]), "+f"(d[83]), "+f"(d[84]), "+f"(d[85]), "+f"(d[86]), "+f"(d[87]), "+f"(d[88]), "+f"(d[89]), "+f"(d[90]), "+f"(d[91]), "+f"(d[92]), "+f"(d[93]), "+f"(d[94]), "+f"(d[95])
    : "l"(da), "l"(db), "r"(sc));
}
__device__ __forceinline__ void wgmma_n192_bk(float* d, uint64_t da, uint64_t db, int sc) {
  asm volatile("{\n.reg .pred p;\nsetp.ne.b32 p, %98, 0;\n"
    "wgmma.mma_async.sync.aligned.m64n192k16.f32.bf16.bf16 {%0, %1, %2, %3, %4, %5, %6, %7, %8, %9, %10, %11, %12, %13, %14, %15, %16, %17, %18, %19, %20, %21, %22, %23, %24, %25, %26, %27, %28, %29, %30, %31, %32, %33, %34, %35, %36, %37, %38, %39, %40, %41, %42, %43, %44, %45, %46, %47, %48, %49, %50, %51, %52, %53, %54, %55, %56, %57, %58, %59, %60, %61, %62, %63, %64, %65, %66, %67, %68, %69, %70, %71, %72, %73, %74, %75, %76, %77, %78, %79, %80, %81, %82, %83, %84, %85, %86, %87, %88, %89, %90, %91, %92, %93, %94, %95}, %96, %97, p, 1, 1, 0, 0;\n}\n"
    : "+f"(d[0]), "+f"(d[1]), "+f"(d[2]), "+f"(d[3]), "+f"(d[4]), "+f"(d[5]), "+f"(d[6]), "+f"(d[7]), "+f"(d[8]), "+f"(d[9]), "+f"(d[10]), "+f"(d[11]), "+f"(d[12]), "+f"(d[13]), "+f"(d[14]), "+f"(d[15]), "+f"(d[16]), "+f"(d[17]), "+f"(d[18]), "+f"(d[19]), "+f"(d[20]), "+f"(d[21]), "+f"(d[22]), "+f"(d[23]), "+f"(d[24]), "+f"(d[25]), "+f"(d[26]), "+f"(d[27]), "+f"(d[28]), "+f"(d[29]), "+f"(d[30]), "+f"(d[31]), "+f"(d[32]), "+f"(d[33]), "+f"(d[34]), "+f"(d[35]), "+f"(d[36]), "+f"(d[37]), "+f"(d[38]), "+f"(d[39]), "+f"(d[40]), "+f"(d[41]), "+f"(d[42]), "+f"(d[43]), "+f"(d[44]), "+f"(d[45]), "+f"(d[46]), "+f"(d[47]), "+f"(d[48]), "+f"(d[49]), "+f"(d[50]), "+f"(d[51]), "+f"(d[52]), "+f"(d[53]), "+f"(d[54]), "+f"(d[55]), "+f"(d[56]), "+f"(d[57]), "+f"(d[58]), "+f"(d[59]), "+f"(d[60]), "+f"(d[61]), "+f"(d[62]), "+f"(d[63]), "+f"(d[64]), "+f"(d[65]), "+f"(d[66]), "+f"(d[67]), "+f"(d[68]), "+f"(d[69]), "+f"(d[70]), "+f"(d[71]), "+f"(d[72]), "+f"(d[73]), "+f"(d[74]), "+f"(d[75]), "+f"(d[76]), "+f"(d[77]), "+f"(d[78]), "+f"(d[79]), "+f"(d[80]), "+f"(d[81]), "+f"(d[82]), "+f"(d[83]), "+f"(d[84]), "+f"(d[85]), "+f"(d[86]), "+f"(d[87]), "+f"(d[88]), "+f"(d[89]), "+f"(d[90]), "+f"(d[91]), "+f"(d[92]), "+f"(d[93]), "+f"(d[94]), "+f"(d[95])
    : "l"(da), "l"(db), "r"(sc));
}
__device__ __forceinline__ void wgmma_n160_bmn(float* d, uint64_t da, uint64_t db, int sc) {
  asm volatile("{\n.reg .pred p;\nsetp.ne.b32 p, %82, 0;\n"
    "wgmma.mma_async.sync.aligned.m64n160k16.f32.bf16.bf16 {%0, %1, %2, %3, %4, %5, %6, %7, %8, %9, %10, %11, %12, %13, %14, %15, %16, %17, %18, %19, %20, %21, %22, %23, %24, %25, %26, %27, %28, %29, %30, %31, %32, %33, %34, %35, %36, %37, %38, %39, %40, %41, %42, %43, %44, %45, %46, %47, %48, %49, %50, %51, %52, %53, %54, %55, %56, %57, %58, %59, %60, %61, %62, %63, %64, %65, %66, %67, %68, %69, %70, %71, %72, %73, %74, %75, %76, %77, %78, %79}, %80, %81, p, 1, 1, 0, 1;\n}\n"
    : "+f"(d[0]), "+f"(d[1]), "+f"(d[2]), "+f"(d[3]), "+f"(d[4]), "+f"(d[5]), "+f"(d[6]), "+f"(d[7]), "+f"(d[8]), "+f"(d[9]), "+f"(d[10]), "+f"(d[11]), "+f"(d[12]), "+f"(d[13]), "+f"(d[14]), "+f"(d[15]), "+f"(d[16]), "+f"(d[17]), "+f"(d[18]), "+f"(d[19]), "+f"(d[20]), "+f"(d[21]), "+f"(d[22]), "+f"(d[23]), "+f"(d[24]), "+f"(d[25]), "+f"(d[26]), "+f"(d[27]), "+f"(d[28]), "+f"(d[29]), "+f"(d[30]), "+f"(d[31]), "+f"(d[32]), "+f"(d[33]), "+f"(d[34]), "+f"(d[35]), "+f"(d[36]), "+f"(d[37]), "+f"(d[38]), "+f"(d[39]), "+f"(d[40]), "+f"(d[41]), "+f"(d[42]), "+f"(d[43]), "+f"(d[44]), "+f"(d[45]), "+f"(d[46]), "+f"(d[47]), "+f"(d[48]), "+f"(d[49]), "+f"(d[50]), "+f"(d[51]), "+f"(d[52]), "+f"(d[53]), "+f"(d[54]), "+f"(d[55]), "+f"(d[56]), "+f"(d[57]), "+f"(d[58]), "+f"(d[59]), "+f"(d[60]), "+f"(d[61]), "+f"(d[62]), "+f"(d[63]), "+f"(d[64]), "+f"(d[65]), "+f"(d[66]), "+f"(d[67]), "+f"(d[68]), "+f"(d[69]), "+f"(d[70]), "+f"(d[71]), "+f"(d[72]), "+f"(d[73]), "+f"(d[74]), "+f"(d[75]), "+f"(d[76]), "+f"(d[77]), "+f"(d[78]), "+f"(d[79])
    : "l"(da), "l"(db), "r"(sc));
}
__device__ __forceinline__ void wgmma_rs_n32(float* d, const uint32_t* a, uint64_t db, int sc) {
  asm volatile("{\n.reg .pred p;\nsetp.ne.b32 p, %21, 0;\n"
    "wgmma.mma_async.sync.aligned.m64n32k16.f32.bf16.bf16 {%0, %1, %2, %3, %4, %5, %6, %7, %8, %9, %10, %11, %12, %13, %14, %15}, {%16, %17, %18, %19}, %20, p, 1, 1, 0;\n}\n"
    : "+f"(d[0]), "+f"(d[1]), "+f"(d[2]), "+f"(d[3]), "+f"(d[4]), "+f"(d[5]), "+f"(d[6]), "+f"(d[7]), "+f"(d[8]), "+f"(d[9]), "+f"(d[10]), "+f"(d[11]), "+f"(d[12]), "+f"(d[13]), "+f"(d[14]), "+f"(d[15])
    : "r"(a[0]), "r"(a[1]), "r"(a[2]), "r"(a[3]), "l"(db), "r"(sc));
}

__device__ __forceinline__ uint32_t gelu2(float a0, float a1, float hr) {
  const float c1 = 8.f * 0.7978845608028654f * 0.044715f, c0 = 2.f * 0.7978845608028654f;
  const float h0 = a0 * hr, h1 = a1 * hr;
  return pack_bf16(fmaf(h0, tanh_fast(h0 * fmaf(h0 * h0, c1, c0)), h0), fmaf(h1, tanh_fast(h1 * fmaf(h1 * h1, c1, c0)), h1));
}
template <int M> __device__ __forceinline__ void conv_frag(uint32_t* f, uint32_t abase) {
  const uint32_t a = abase + 256 * M;
  f[0] = lds32(a); f[1] = lds32(a + 128); f[2] = lds32(a + 16); f[3] = lds32(a + 144);
}
constexpr uint32_t ONE2 = 0x3f803f80u;

struct BaseCtx { uint32_t nm[2], rs[2], xa, za, ba; };
__device__ __forceinline__ BaseCtx base_ctx(uint32_t sb, int half, int w, int lane) {
  const int mi = lane >> 3, li = lane & 7, xr = (mi & 1) * 8 + li;
  const float2 st0 = lds64f(sb + SSTAT + (half * 64 + 16 * w + (lane >> 2)) * 8), st1 = lds64f(sb + SSTAT + (half * 64 + 16 * w + (lane >> 2) + 8) * 8);
  return {{pack_bf16(-st0.x, -st0.x), pack_bf16(-st1.x, -st1.x)}, {pack_bf16(st0.y, st0.y), pack_bf16(st1.y, st1.y)},
          sb + FIN_X + w * 5120 + xr * 64 + (((mi >> 1) ^ ((xr >> 1) & 3)) << 4),
          sb + FIN_Z + (8 * (mi >> 1) + li) * 128 + (((2 * w + (mi & 1)) ^ li) << 4), sb + SB2 + 4 * (lane & 3)};
}
__device__ __forceinline__ void base_block(const BaseCtx& k, int q) {
  uint32_t xv[8], zv[8], bv[4];
  const uint32_t xa = k.xa + q * 1024, za = k.za + q * 4096;
  ldsm4(xa, xv); ldsm4(xa ^ 32, xv + 4);
  ldsm4t(za, zv); ldsm4t(za + 2048, zv + 4);
#pragma unroll
  for (int g = 0; g < 4; g++) bv[g] = lds32(k.ba + q * 64 + 16 * g);
#pragma unroll
  for (int e = 0; e < 8; e++) xv[e] = bfma2(bmul2(bfma2(xv[e], ONE2, k.nm[e & 1]), k.rs[e & 1]), zv[e], bfma2(xv[e], ONE2, bv[e >> 1]));
  stsm4(xa, xv[0], xv[1], xv[2], xv[3]); stsm4(xa ^ 32, xv[4], xv[5], xv[6], xv[7]);
}

struct Params {
  const __nv_bfloat16 *x, *k, *v, *shift_k, *ssm_k, *ssm_D, *w1p, *b1, *w2p, *b2;
  CUtensorMap x_a, w1, kt, vt, ut, h, w2, w2h, x_t, out, w23;
};

__global__ void __launch_bounds__(512, 1) fused_kernel(const __grid_constant__ Params P) {
  extern __shared__ __align__(1024) uint8_t smem[];
  const uint32_t sb = smem_u32(smem);
  const int tid = threadIdx.x, lane = tid & 31;
  const int warp = __shfl_sync(~0u, tid >> 5, 0), wg = warp >> 2;
  const int b = blockIdx.x;
  const int strip = b >> 5, slice = (b >> 2) & 7;
  const int rb128 = 4 * strip + (b & 3);
  const int rb64 = 2 * rb128 + (slice >> 2), ns = slice & 3;
  const int rot = ns & 1;
  const int d0 = 160 * (b >> 5) + (b & 31);
#define BAR(i) (sb + BARS + 8 * (i))
  const unsigned t0 = clock();

  if (warp < 9) {
    if (elect_one()) {
#pragma unroll
      for (int k = 0; k < 10; k++) mbar_init(BAR(10 * warp + k), 1 << ((0x3AA40 >> (2 * warp)) & 3));
      asm volatile("fence.mbarrier_init.release.cluster;\n" ::: "memory");
    }
    __syncwarp();
    asm volatile("bar.arrive 4, 320;\n" ::: "memory");
  } else if (warp == 12) {
    bar_sync(4, 320);
#pragma unroll 1
    for (int kt = 0; kt < 4; kt++) {
      if (elect_one()) {
        TL(74 + kt);
        mbar_expect(BAR(B_FULL1 + kt), ST1_BYTES);
        tma2d(sb + kt * ST1_BYTES, &P.x_a, kt * 64, rb128 * 128, BAR(B_FULL1 + kt));
        tma3d(sb + kt * ST1_BYTES + ST1_B, &P.w1, 0, kt * 64, slice * 3, BAR(B_FULL1 + kt));
      }
    }
    if (elect_one()) {
      mbar_expect(BAR(B_XSH), 20480);
      bulk_g2s(sb + XSH, P.x + (128 * rb128 + 16 * slice) * D_, 20480, BAR(B_XSH));
      l2_prefetch(P.w1p + (256 + 3 * b) * F_, 3 * F_ * 2);
    }
  }

  if (wg == 3) {
    asm volatile("setmaxnreg.dec.sync.aligned.u32 64;\n");
    if (warp != 12) bar_sync(0, 480);
    if (warp == 12) {
#pragma unroll 1
      for (int kt = 4; kt < 10; kt++) {
        const int s = kt & 3;
        mbar_wait(BAR(B_EMPTY1 + s), kt >> 3);
        if (elect_one()) {
          mbar_expect(BAR(B_FULL1 + s), ST1_BYTES);
          tma2d(sb + s * ST1_BYTES, &P.x_a, kt * 64, rb128 * 128, BAR(B_FULL1 + s));
          tma3d(sb + s * ST1_BYTES + ST1_B, &P.w1, 0, kt * 64, slice * 3, BAR(B_FULL1 + s));
        }
      }
      const int nb0 = (160 * ns + 32 * rot) >> 6;
      const int nrem = 160 * ns + (rot ? 0 : 128);
      const uint32_t own = sb + HST + (rb64 & 1) * 3 * 8192, oth = sb + HST + ((rb64 & 1) ^ 1) * 3 * 8192;
      int k0 = slice * 192, s = 0, par = 1;
      mbar_wait(BAR(B_EMPTY1 + 2), 1);
      mbar_wait(BAR(B_EMPTY1 + 3), 1);
#pragma unroll 1
      for (int kt = 0; kt < 24; kt++) {
        mbar_wait(BAR(B_EMPTY2 + s), par);
        if (kt == (W2_EARLY ? 3 : 0)) { mbar_wait(BAR(B_G1DONE), 0); mbar_wait(BAR(B_UFULL), 0); }
        if (kt == 4) { mbar_wait(BAR(B_HRD), 0); mbar_wait(BAR(B_EMPTY2 + 2), 0); }
        const uint32_t bs = s == 4 ? own : sb + R2B + ((s + 1) & 3) * ST2B_BYTES;
        if (elect_one()) {
          const bool three = W23 && !rot;
          mbar_expect(BAR(B_FULL2 + s), (three ? 24576 : 20480) + (kt < 3 ? 0 : 8192));
          tma3d(bs, three ? &P.w23 : &P.w2, 0, k0, nb0, BAR(B_FULL2 + s));
          if (!three) tma2d(bs + 16384, &P.w2h, nrem, k0, BAR(B_FULL2 + s));
        }
        if (kt >= 3) {
          if (kt == 3 || kt == 10) {
            mbar_wait(BAR(B_HRDY + (kt >> 3)), 0);
            fence_async();
            if (lane == 0) TL(2 + (kt >> 3));
          }
          if (elect_one()) {
            tma2d(s < 3 ? oth + s * 8192 : sb + R2A + (s - 3) * 8192, &P.h, k0, rb64 * 64, BAR(B_FULL2 + s));
          }
        }
        if (kt < 2) k0 += 64;
        else if (kt == 2) k0 = slice == 0 ? 192 : 0;
        else {
          k0 += 192;
          if ((unsigned)(k0 - slice * 192) < 192u) k0 += 192;
          if (k0 >= F_) k0 -= slice == 0 ? F_ - 256 : F_ - 64;
        }
        if (++s == 5) { s = 0; par ^= 1; }
      }
    } else if (warp == 13) {
      if (elect_one()) {
        mbar_expect(BAR(B_KV), 22400 + 20480 + 2560 + 320);
        bulk_g2s(sb + SB2, P.b2 + ns * 160, 320, BAR(B_KV));
      }
      const int jit = (b * 37) & 127;
#pragma unroll 1
      for (int i = 0; i < 10; i++) {
        wait_until(t0 + KV_T + (jit * KV_STEP >> 7) + i * KV_STEP);
        if (elect_one()) {
          tma3d(sb + (i < 5 ? KV_K + i * 4480 : KV_V - 5 * 4096 + i * 4096), i < 5 ? &P.kt : &P.vt, 0, 32 * (b >> 1) - (i < 5 ? 3 : 0),
                5 * (b & 1) + (i < 5 ? i : i - 5), BAR(B_KV));
          if (i == 0) bulk_g2s(sb + SHK, P.shift_k + 320 * (b & 1) * 4, 2560, BAR(B_KV));
        }
      }
      if (lane == 0) TL(39);
#pragma unroll 1
      for (int i = 0; i < 9; i++) {
        const __nv_bfloat16* p = (i >= 2 && i < 6 ? P.w2p + b * 12 * D_ + (i - 2) * 2048 : P.ssm_k + (d0 + 32 * (i < 2 ? i : i - 4)) * S_) + lane * 64;
        wait_until(t0 + PF_T + (jit * PF_STEP >> 7) + i * PF_STEP);
        if (i != 5 || lane < 24) prefetch_l2(p);
      }
      const float dd = __bfloat162float(P.ssm_D[d0 + 32 * (lane < 5 ? lane : 0)]);
      const unsigned ep = read_epoch();
#pragma unroll 1
      for (int ch = 0; ch < 5; ch++) {
        const uint32_t cb = sb + CONV + (ch & 1) * CB_BYTES;
        uint4 e[8];
        uint32_t pv[8];
#pragma unroll
        for (int r = 0; r < 8; r++) e[r] = ldg128(P.ssm_k + (d0 + 32 * ch) * S_ + (lane + 32 * r) * 8);
        const float dch = __shfl_sync(~0u, dd, ch);
        if (lane == 0) e[0].x = (e[0].x & 0xffff0000u) | (pack_bf16(bf_lo(e[0].x) + dch, 0.f) & 0xffffu);
#pragma unroll
        for (int r = 0; r < 8; r++) pv[r] = __shfl_sync(~0u, e[r].w, (lane + 31) & 31);
        if (ch == 0) {
          mbar_wait(BAR(B_KVFREE), 0);
          if (lane < 20) {
            const int off = lane < 18 ? 4096 + lane * 16 : lane == 18 ? CB_E : CB_O;
            sts128(sb + CONV + off, 0, 0, 0, 0);
            sts128(sb + CONV + CB_BYTES + off, 0, 0, 0, 0);
            if (lane < 18) sts128(sb + U3 + off, 0, 0, 0, 0);
            fence_async_smem();
          }
        }
        if (ch >= 2) mbar_wait(BAR(B_EOFREE + (ch & 1)), ch >> 2);
#pragma unroll
        for (int r = 7; r >= 0; r--) {
          sts128(cb + CB_E + 16 + (lane + 32 * r) * 16, e[r].x, e[r].y, e[r].z, e[r].w);
          sts128(cb + CB_O + 16 + (lane + 32 * r) * 16, __byte_perm(lane ? pv[r] : r ? pv[r ? r - 1 : 0] : 0u, e[r].x, 0x5432),
                 __byte_perm(e[r].x, e[r].y, 0x5432), __byte_perm(e[r].y, e[r].z, 0x5432), __byte_perm(e[r].z, e[r].w, 0x5432));
        }
        if (ch == 1) {
          mbar_wait(BAR(B_UFULL), 0);
          ld_tagged<8, 1>(e, g_u + (d0 + 32) * S_ + lane * 8, 256, 0, tag_bits(ep));
          mbar_wait(BAR(B_PUB2), 0);
#pragma unroll
          for (int r = 0; r < 8; r++) sts128(cb + (lane + 32 * r) * 16, e[r].x, e[r].y, e[r].z, e[r].w);
          fence_async_smem();
        }
        __syncwarp();
        if (lane < (ch < 2 ? 2 : 1)) mbar_arrive(BAR(B_CFULL + (ch & 1)));
        if (ch >= 1 && ch < 4) {
          if (ch == 1) { flag_wait(FL_U, 128 * ep); fence_async(); }
          else mbar_wait(BAR(B_CEMPTY + (ch & 1)), 0);
          if (elect_one()) {
            mbar_expect(BAR(B_CFULL + (~ch & 1)), 4096);
            bulk_g2s(ch == 1 ? sb + U3 : cb, g_u + (d0 + 32 * ch + 32) * S_, 4096, BAR(B_CFULL + (~ch & 1)));
          }
        }
      }
      mbar_wait(BAR(B_REMPTY + 1), 1);
      if (elect_one()) {
        mbar_expect(BAR(B_FINX), 20480);
#pragma unroll 1
        for (int i = 0; i < 4; i++) tma3d(sb + FIN_X + i * 5120, &P.x_t, 0, rb64 * 64 + i * 16, ns * 5, BAR(B_FINX));
      }
    } else {
      const int j = warp - 14;
      const unsigned ep = read_epoch();
      {
        uint4 pk[8];
        const uint4* pp = g_pb + slice * 96 + lane + 32 * j;
        const uint4* pa = j == 0 ? g_pa + rb128 * 128 + lane : pp;
        const int sa = j == 0 ? 32 : F_ / 2;
        if (j == 1) pp += 32;
#pragma unroll
        for (int i = 0; i < 8; i++) pk[i].w = ~ep;
        wait_until(t0 + AUG_T);
        if (j == 1) {
          wait_until(t0 + TM_T);
#pragma unroll 1
          for (int i = 2; i < 11; i++) if (elect_one()) tmap_prefetch(&P.x_a + i);
        }
#pragma unroll 1
        for (int it = 0; it < (1 << 12); it++) {
          bool ok = true;
#pragma unroll
          for (int i = 0; i < 8; i++)
            if (pk[i].w != ep) pk[i] = ld_pkt(i < 4 ? pa + i * sa : pp + (i - 4) * (F_ / 2));
#pragma unroll
          for (int i = 0; i < 8; i++) ok = ok && pk[i].w == ep;
          if (__all_sync(~0u, ok)) break;
          wait_until(t0 + AUG2_T);
          __nanosleep(LL_SLEEP);
        }
        if (lane == 0 && j == 0) TL(16);
        mbar_wait(BAR(B_XFREE), 0);
        if (j == 0) {
#pragma unroll
          for (int i = 0; i < 4; i++) {
            const uint32_t hh = __byte_perm(pk[i].x, 0, 0x1010), a = sb + AUG_A + (lane >> 3) * 256 + (lane & 7) * 16 + i * 1024;
            sts128(a, hh, __byte_perm(pk[i].x, pk[i].y, 0x5432), hh, __byte_perm(pk[i].x, pk[i].y, 0x7632));
            sts128(a + 128, hh, pk[i].x >> 16, hh, pk[i].x >> 16);
            sts64f(sb + SSTAT + lane * 8 + i * 256, -(bf_lo(pk[i].x) + bf_hi(pk[i].x)), __uint_as_float(pk[i].z));
          }
        }
#pragma unroll 1
        for (int g = 1; g >= 1 - j; g--) {
          const uint32_t a = sb + AUG_B + (lane >> 2) * 256 + (lane & 3) * 32 + (j == 0 ? 0 : 2048 + 2048 * g);
          sts128(a, pk[4].x, __byte_perm(pk[4].x, pk[4].z, 0x5410), pk[5].x, __byte_perm(pk[5].x, pk[5].z, 0x5410));
          sts128(a + 128, pk[6].x, pk[6].x & 0xffffu, pk[7].x, pk[7].x & 0xffffu);
          sts128(a + 16, pk[4].y, __byte_perm(pk[4].y, pk[4].z, 0x7610), pk[5].y, __byte_perm(pk[5].y, pk[5].z, 0x7610));
          sts128(a + 144, pk[6].y, pk[6].y & 0xffffu, pk[7].y, pk[7].y & 0xffffu);
#pragma unroll
          for (int i = 0; i < 4; i++) pk[4 + i] = pk[i];
        }
        fence_async_smem();
        __syncwarp();
        if (lane == 0) { mbar_arrive(BAR(B_AUG)); if (j == 0) TL(17); }
      }
      if (j == 0) {
#pragma unroll 1
        for (int ch = 0; ch < 6; ch++) {
          const int g = ch & 1, c = ch >> 1;
          mbar_wait(BAR(B_HCH + 3 * g + c), 0);
          if (ch == H_AFTER_U) mbar_wait(BAR(B_UFULL), 0);
          if (elect_one()) {
            tma2d_store(&P.h, slice * 192 + c * 64, rb128 * 128 + 64 * g, sb + HST + (3 * g + c) * 8192);
            if (ch == 1 || ch == 5) {
              TL(51 + c);
              bulk_commit();
              bulk_wait<0>();
              mbar_arrive(BAR(ch == 1 ? B_H0 : B_HRD));
              if (ch == 5) { flag_arrive(FL_H + 2 * rb128 + 1); TL(11); }
            }
          }
          __syncwarp();
        }
      } else {
        mbar_wait(BAR(B_PUB2), 0);
        if (SEP_U && elect_one()) flag_arrive(FL_U);
        mbar_wait(BAR(B_H0), 0);
        if (elect_one()) { flag_arrive(FL_H + 2 * rb128); if (!SEP_U) flag_arrive_relaxed(FL_U); TL(9); }
#pragma unroll 1
        for (int c = 0; c < 2; c++) {
          flag_wait(FL_H + 2 * rb128 + c, 8 * ep);
          if (elect_one()) mbar_arrive(BAR(B_HRDY + c));
        }
        if (!ZH_D) {
          mbar_wait(BAR(B_TOK + 8), 0);
          flag_wait_relaxed(FL_ZH + ns, 128 * ep);
          if (elect_one()) mbar_arrive(BAR(B_ZRDY));
        }
      }
    }
  } else if (wg == 2) {
    asm volatile("setmaxnreg.inc.sync.aligned.u32 192;\n");
    const int t = tid & 127, w = warp & 3, b0 = lane >> 2, c = lane & 3;
    bar_sync(0, 480);
    const unsigned ep = read_epoch();
    const uint32_t tag = tag_bits(ep);
    {
      uint4 wv[8];
      const int tc = t < 120 ? t : 119, cc = tc % 6, rg = tc / 6;
      const __nv_bfloat16* wr = P.w1p + (160 * (rb128 >> 2) + 8 * rg) * F_ + slice * 192 + (rb128 & 3) * 48 + cc * 8;
      const uint32_t b1v = ldg32(P.b1 + slice * 192 + (rb128 & 3) * 48 + (t < 96 ? (t >> 2) * 2 : 0));
      wait_until(t0 + W1_T);
#pragma unroll
      for (int j = 0; j < 8; j++) wv[j] = ldg128(wr + j * F_);
      mbar_wait(BAR(B_XSH), 0);
      if (t == 0) TL(18);
      const uint32_t xsa = sb + XSH + (4 * w + (lane >> 3)) * 1280 + (lane & 7) * 16;
      uint4 xv[2] = {lds128(xsa), lds128(xsa + 128)};
      const uint32_t x0w = __shfl_sync(~0u, xv[0].x, lane & 24);
      const uint32_t nx0 = __byte_perm(x0w, 0, 0x1010) ^ 0x80008000u;
      float s4[4] = {0.f, 0.f, 0.f, 0.f}, q4[4] = {0.f, 0.f, 0.f, 0.f};
#pragma unroll 1
      for (uint32_t a = xsa + 256; a < xsa + 1536; a += 256) {
#pragma unroll
        for (int h = 0; h < 2; h++) {
          uint32_t dd[4];
          dd[0] = bfma2(xv[h].x, ONE2, nx0); dd[1] = bfma2(xv[h].y, ONE2, nx0); dd[2] = bfma2(xv[h].z, ONE2, nx0); dd[3] = bfma2(xv[h].w, ONE2, nx0);
          xv[h] = lds128(a + h * 128);
#pragma unroll
          for (int e = 0; e < 4; e++) {
            const float a0 = bf_lo(dd[e]), a1 = bf_hi(dd[e]);
            s4[e] += a0 + a1;
            q4[e] = fmaf(a0, a0, fmaf(a1, a1, q4[e]));
          }
        }
      }
      __syncwarp();
      if (lane == 0) mbar_arrive(BAR(B_XFREE));
      float s = (s4[0] + s4[1]) + (s4[2] + s4[3]), q = (q4[0] + q4[1]) + (q4[2] + q4[3]);
#pragma unroll
      for (int m = 1; m < 8; m <<= 1) { s += __shfl_xor_sync(~0u, s, m); q += __shfl_xor_sync(~0u, q, m); }
      s *= 1.f / D_;
      const float mu = -(bf_lo(x0w) + s), ve = fmaxf(q * (1.f / D_) - s * s, 0.f) + 1e-5f;
      const float r0 = rsqrtf(ve), rs = r0 * fmaf(-0.5f * ve * r0, r0, 1.5f), sg = ve * rs;
      const float mh = bf_round(mu), sh = bf_round(sg);
      if ((lane & 7) == 0)
        st_pkt(g_pa + 128 * rb128 + 16 * slice + 4 * w + (lane >> 3), pack_bf16(mh, mu - mh), pack_bf16(sh, sg - sh), __float_as_uint(rs), ep);
      if (t == 0) TL(14);
      float cs[8];
#pragma unroll
      for (int e = 0; e < 8; e++) cs[e] = 0.f;
#pragma unroll
      for (int j = 0; j < 8; j++) {
        cs[0] += bf_lo(wv[j].x); cs[1] += bf_hi(wv[j].x); cs[2] += bf_lo(wv[j].y); cs[3] += bf_hi(wv[j].y);
        cs[4] += bf_lo(wv[j].z); cs[5] += bf_hi(wv[j].z); cs[6] += bf_lo(wv[j].w); cs[7] += bf_hi(wv[j].w);
      }
      mbar_wait(BAR(B_XFREE), 0);
      if (t < 120) {
        const uint32_t a = sb + CS_TMP + (rg * 48 + cc * 8) * 4;
        sts128(a, __float_as_uint(cs[0]), __float_as_uint(cs[1]), __float_as_uint(cs[2]), __float_as_uint(cs[3]));
        sts128(a + 16, __float_as_uint(cs[4]), __float_as_uint(cs[5]), __float_as_uint(cs[6]), __float_as_uint(cs[7]));
      }
      bar_sync(1, 128);
      if (w < 3) {
        float p[10];
#pragma unroll
        for (int j = 0; j < 10; j++) p[j] = __uint_as_float(lds32(sb + CS_TMP + ((2 * j + (t & 1)) * 48 + (t >> 1)) * 4));
        float g = ((p[0] + p[1]) + (p[2] + p[3])) + ((p[4] + p[5]) + (p[6] + p[7])) + (p[8] + p[9]);
        g += __shfl_xor_sync(~0u, g, 1);
        const float gh = bf_round(g);
        const uint32_t pk = pack_bf16(gh, g - gh), pk1 = __shfl_xor_sync(~0u, pk, 2);
        if ((t & 3) == 0) st_pkt(g_pb + (rb128 >> 2) * (F_ / 2) + slice * 96 + (rb128 & 3) * 24 + (t >> 2), pk, pk1, rb128 < 8 ? b1v : 0u, ep);
      }
      if (t == 0) TL(15);
    }
    {
      mbar_wait(BAR(B_KV), 0);
      if (ADAPT && lane == 0) mbar_arrive(BAR(B_PUB1));
      if (KV_GATE) mbar_wait(BAR(B_G1MAIN), 0);
      if (t == 0) TL(40);
      const int rA = 8 * (lane >> 3), cA = 64 * w + 8 * (lane & 7);
      const int rB = 16 * (w >> 1) + 8 * (lane & 1), cB = 32 * (w & 1) + 2 * (lane >> 1);
      uint32_t kk[11][5], q[8][5];
      uint4 sw[5];
      {
        const uint32_t ka = sb + KV_K + w * 4480 + rA * 128 + (lane & 7) * 16, va = sb + KV_V + w * 4096 + rA * 128 + (lane & 7) * 16;
        const uint32_t kb = sb + KV_K + 4 * 4480 + rB * 128 + cB * 2, vb = sb + KV_V + 4 * 4096 + rB * 128 + cB * 2;
#define LDS4(dst, a) { const uint4 v_ = lds128(a); dst[0] = v_.x; dst[1] = v_.y; dst[2] = v_.z; dst[3] = v_.w; }
#pragma unroll
        for (int e = 0; e < 5; e++) sw[e] = lds128(sb + SHK + (e < 4 ? cA * 8 + e * 16 : (256 + cB) * 8));
#pragma unroll
        for (int r = 0; r < 11; r++) { LDS4(kk[r], ka + r * 128) kk[r][4] = lds32(kb + r * 128); }
#pragma unroll
        for (int r = 0; r < 8; r++) { LDS4(q[r], va + r * 128) q[r][4] = lds32(vb + r * 128); }
        __syncwarp();
        if (lane == 0) mbar_arrive(BAR(B_KVFREE));
        if (t == 0) TL(13);
      }
#pragma unroll
      for (int e = 0; e < 5; e++) {
        const uint32_t w0 = __byte_perm(sw[e].x, sw[e].z, 0x5410), w1 = __byte_perm(sw[e].x, sw[e].z, 0x7632);
        const uint32_t w2 = __byte_perm(sw[e].y, sw[e].w, 0x5410), w3 = __byte_perm(sw[e].y, sw[e].w, 0x7632);
#pragma unroll
        for (int r = 0; r < 8; r++) q[r][e] = bmul2(bfma2(kk[r + 3][e], w0, bfma2(kk[r + 2][e], w1, bfma2(kk[r + 1][e], w2, bmul2(kk[r][e], w3)))), q[r][e]);
        if (e == 0) mbar_wait(BAR(B_KVFREE), 0);
        const uint32_t ua = e < 4 ? sb + UST + w * 4096 + (lane & 4) * 512 + e * 512 + (lane & 3) * 64 + (((3 - (lane >> 3)) ^ ((lane >> 1) & 1)) << 4)
                                  : sb + UST4 + (w & 1) * 2048 + (cB & 7) * 256 + ((cB >> 3) & 3) * 64 + (((3 - (rB >> 3)) ^ ((cB >> 4) & 1)) << 4);
        sts128(ua, (__byte_perm(q[7][e], q[6][e], 0x5410) & ~0x00010001u) | tag, __byte_perm(q[5][e], q[4][e], 0x5410),
               __byte_perm(q[3][e], q[2][e], 0x5410), __byte_perm(q[1][e], q[0][e], 0x5410));
        sts128((ua ^ 32) + 256, (__byte_perm(q[7][e], q[6][e], 0x7632) & ~0x00010001u) | tag, __byte_perm(q[5][e], q[4][e], 0x7632),
               __byte_perm(q[3][e], q[2][e], 0x7632), __byte_perm(q[1][e], q[0][e], 0x7632));
      }
      fence_async_smem();
      bar_sync(1, 128);
      if (t == 0) TL(12);
      const unsigned tst = clock();
      if (U_AFTER_AUG) mbar_wait(BAR(B_AUG), 0);
      if (w == 0 && elect_one()) {
#pragma unroll 1
        for (int i = 0; i < 10; i++) {
          const int u = (i >> 1) + 5 * (i & 1);
          if (i == U_LATE) { bulk_commit(); mbar_wait(BAR(B_H0), 0); }
          tma4d_store(&P.ut, 2016 - 32 * (b >> 1), 10 * (b & 1) + u, sb + (u < 8 ? UST + u * 2048 : UST4 - 8 * 2048 + u * 2048));
          if (i == 1) { if (UH_WAIT && !UH_D) { bulk_commit(); bulk_wait<0>(); } if (!UH_D) flag_arrive_relaxed(FL_UH); TL(7); }
        }
        bulk_commit();
        bulk_wait<0>();
        mbar_arrive(BAR(B_PUB2));
      }
      if (t == 0) TL(19);
      if (UH_D) wait_until(tst + UH_D); else flag_wait_relaxed(FL_UH, 128 * ep);
      if (t == 0) TL(6);
      if (UH_DELAY) __nanosleep(UH_DELAY);
      uint4 uu[2];
      ld_tagged<2, 1>(uu, g_u + d0 * S_ + t * 8, 1024, 0, tag);
      if (t == 0) TL(8);
      sts128(sb + CONV + t * 16, uu[0].x, uu[0].y, uu[0].z, uu[0].w);
      sts128(sb + CONV + 2048 + t * 16, uu[1].x, uu[1].y, uu[1].z, uu[1].w);
      fence_async_smem();
      __syncwarp();
      if (lane == 0) mbar_arrive(BAR(B_UFULL));
    }
    {
      const int x0 = 16 * w + b0 + 2 * c - 7;
      const uint32_t foff = sb + CONV + ((b0 & 1) ? CB_E + (x0 + 8) * 2 : CB_O + (x0 + 9) * 2);
      const uint32_t dump = sb + RED + w * RED_P + (31 - lane + 2 * w) * 16;
      uint32_t f[4][8];
      float d[128];
      unsigned tr[10];
#define CONV_MMA(M, Sl)                                                                                      \
  {                                                                                                          \
    if ((M) == 0) wgmma_rs_n32_init(d + 16 * (Sl), f[0], hd + (uint64_t)(32 * (7 - (Sl))));                  \
    else wgmma_rs_n32(d + 16 * (Sl), f[((M) >> 1) & 3] + 4 * ((M) & 1), hd + (uint64_t)(32 * (7 - (Sl)) + 16 * (M)), 1); \
  }
#define CONV_FRAG(T, a) { conv_frag<2 * (T)>(f[(T) & 3], a); conv_frag<2 * (T) + 1>(f[(T) & 3] + 4, a); }
#define CONV_DUMP(Sl)                                                                                        \
  {                                                                                                          \
    uint32_t pk[4];                                                                                          \
    _Pragma("unroll") for (int g = 0; g < 4; g++) {                                                          \
      const int e = 16 * (Sl) + 4 * g, e2 = g < 3 ? e + 6 : (Sl) > 0 ? 16 * (Sl) - 14 : 0;                   \
      pk[g] = (g < 3 || (Sl) > 0) ? pack_bf16(d[e] + d[e2], d[e + 1] + d[e2 + 1]) : pack_bf16(d[e], d[e + 1]); \
    }                                                                                                        \
    stsm4t(dp + (Sl) * 512, pk[0], pk[1], pk[2], pk[3]);                                                     \
  }
#define CONV_SIG(Bk) { __syncwarp(); if (lane == 0) mbar_arrive(rf + 8 * (Bk)); }
#define CONV_ROW(T)                                                                                          \
  {                                                                                                          \
    if (T >= 2) wg_wait<1>();                                                                                \
    CONV_FRAG(T + 2, ab)                                                                                     \
    wg_fence();                                                                                              \
    CONV_MMA(2 * T, 7) CONV_MMA(2 * T, 6)                                                                    \
    if (T >= 2) CONV_DUMP(T >= 2 ? T - 2 : 0)                                                                \
    _Pragma("unroll") for (int bk = 5; bk >= T; bk--) CONV_MMA(2 * T, bk)                                    \
    if (T >= 2) CONV_SIG(T >= 2 ? T - 2 : 0)                                                                 \
    _Pragma("unroll") for (int bk = 7; bk >= T; bk--) CONV_MMA(2 * T + 1, bk)                                \
    wg_commit();                                                                                             \
    if (TL_ROWS) tr[T] = clock();                                                                            \
  }
      mbar_wait(BAR(B_CFULL), 0);
      CONV_FRAG(0, foff) CONV_FRAG(1, foff)
      uint32_t ab = foff, dp = dump, rf = BAR(B_RFULL), wr = BAR(B_PUB2), cf = BAR(B_CFULL + 1);
      uint32_t sg1 = lane ? BAR(B_TOK + 1) : BAR(B_EOFREE), sg2 = lane == 2 ? BAR(B_CEMPTY) : BAR(B_RFULL + 6 + lane);
      const uint32_t x_ab = foff ^ (foff + CB_BYTES), x_dp = dump ^ (dump + RED_BUF);
      const uint32_t x_sg2 = lane == 2 ? BAR(B_CEMPTY) ^ BAR(B_CEMPTY + 1) : sg2 ^ (sg2 + 64);
      const bool p1 = lane == 0 || t == 1;
      mbar_wait(BAR(B_UFULL), 0);
      if (CONV_GATE) mbar_wait(BAR(B_G1DONE), 0);
#pragma unroll 1
      for (int ch = 0; ch < 5; ch++) {
        const uint32_t abn = ab ^ x_ab;
        const uint64_t hd = mk_desc(sb + (ch == 2 ? U3 : CONV + (ch == 1 || ch == 4) * CB_BYTES), 16, 128, 0);
        if (t == 0 && (TL_ALL || ch == 0 || ch == 2)) TL(20 + 3 * ch);
        if (TL_ROWS) tr[9] = clock();
        CONV_ROW(0)
        mbar_wait(wr, ch >> 2);
        CONV_ROW(1) CONV_ROW(2)
        if (t == 1) mbar_arrive(sg1 - 8);
        CONV_ROW(3) CONV_ROW(4)
        if (ch < 4) mbar_wait(cf, (ch + 1) >> 1 & 1);
        CONV_ROW(5)
        wg_wait<1>();
        CONV_FRAG(0, abn)
        wg_fence();
        CONV_MMA(12, 7) CONV_MMA(12, 6) CONV_DUMP(4) CONV_MMA(13, 7) CONV_MMA(13, 6) CONV_SIG(4) CONV_MMA(14, 7) CONV_MMA(15, 7)
        wg_commit();
        if (TL_ROWS) tr[6] = clock();
        if (p1) mbar_arrive(sg1);
        wg_wait<1>();
        CONV_FRAG(1, abn)
        CONV_DUMP(5) CONV_SIG(5)
        wg_wait<0>();
        if (TL_ROWS) tr[7] = clock();
        if (t == 0 && (TL_ALL || ch == 4)) TL(21 + 3 * ch);
        CONV_DUMP(6) CONV_DUMP(7)
        __syncwarp();
        if (lane < 3) mbar_arrive(sg2);
        ab = abn; dp ^= x_dp; sg2 ^= x_sg2;
        rf ^= BAR(B_RFULL) ^ BAR(B_RFULL + 8);
        cf ^= BAR(B_CFULL) ^ BAR(B_CFULL + 1);
        sg1 = lane ? sg1 + 16 : sg1 ^ BAR(B_EOFREE) ^ BAR(B_EOFREE + 1);
        wr = ch == 0 ? BAR(B_G1DONE) : BAR(B_REMPTY + (~ch & 1));
      }
    }
    {
      const unsigned tce = clock();
      const BaseCtx k = base_ctx(sb, rb64 & 1, w, lane);
      mbar_wait(BAR(B_FINX), 0);
      mbar_wait(BAR(B_RDONE), 0);
      if (t == 0) TL(56);
      const __nv_bfloat16* zp = g_z + (ns * 160 + 128 + (t >> 3)) * S_ + rb64 * 64 + (t & 7) * 8;
      uint4 zz[2];
#pragma unroll 1
      for (int q = 2; q < 5; q++) {
        if (q == 3) {
          if (ZH_D) wait_until(tce + ZH_D); else mbar_wait(BAR(B_ZRDY), 0);
          if (t == 0) TL(35);
          zz[0] = ld_pkt(reinterpret_cast<const uint4*>(zp));
          zz[1] = ld_pkt(reinterpret_cast<const uint4*>(zp + 16 * S_));
        }
        if (q == 4) {
          ld_tagged<2, 1, false>(zz, zp, 16 * S_, 0, tag);
          if (t == 0) TL(36);
          const uint32_t zs = sb + FIN_Z + 16384 + (t >> 3) * 128 + (((t & 7) ^ ((t >> 3) & 7)) << 4);
          sts128(zs, zz[0].x, zz[0].y, zz[0].z, zz[0].w);
          sts128(zs + 2048, zz[1].x, zz[1].y, zz[1].z, zz[1].w);
          bar_sync(1, 128);
        }
        base_block(k, q);
      }
      __syncwarp();
      if (lane == 0) mbar_arrive(BAR(B_BASE));
      if (t == 0) TL(37);
    }
  } else {
    bar_sync(0, 480);
    if (FW && wg == 1) {
      const __nv_bfloat16* xs = P.x + (128 * rb128 + 16 * slice + (lane >> 1)) * D_ + (lane & 1) * 64;
      if (warp == 4) { if (lane < 10) asm volatile("prefetch.L2 [%0];\n" ::"l"(&P.x_a + lane) : "memory"); }
      else if (warp == 5) { prefetch_l2(xs); prefetch_l2(xs + 128); }
      else if (warp == 6 || lane < 16) prefetch_l2(P.w1p + 2 * b * F_ + lane * 64 + (warp - 6) * 2048);
    }
    const int w = warp & 3, b0 = lane >> 2;
    const int mi = lane >> 3, li = lane & 7;
    {
      float acc[96];
      bool paused = false;
#pragma unroll 1
      for (int kt = 0; kt < 10; kt++) {
        const int s = kt & 3;
        const uint32_t st = sb + s * ST1_BYTES;
        const uint64_t da = mk_desc(st + wg * 8192, 16, 1024, 1), db = mk_desc(st + ST1_B, 8192, 1024, 1);
        if (ADAPT ? (kt >= PAUSE2 && !paused && wg_any(mbar_try_nb(BAR(B_PUB1), 0), 5 + wg)) : kt == PAUSE2) {
          paused = true;
          if (lane == 0) mbar_arrive(BAR(B_G1MAIN));
          mbar_wait(BAR(B_KVFREE), 0);
        }
        mbar_wait(BAR(B_FULL1 + s), (kt >> 2) & 1);
        if (tid == 0) TL(64 + kt);
        wg_fence();
#pragma unroll
        for (int kk = 0; kk < 4; kk++) wgmma_n192_bmn(acc, da + 2 * kk, db + 128 * kk, (kt | kk) != 0);
        wg_commit();
        if (kt > 0) { wg_wait<1>(); if (lane == 0) mbar_arrive(BAR(B_EMPTY1 + ((kt - 1) & 3))); }
      }
      if (!paused && lane == 0) mbar_arrive(BAR(B_G1MAIN));
      if (tid == 0) TL(41);

      mbar_wait(BAR(B_AUG), 0);
      wg_fence();
      wgmma_n192_bk(acc, mk_desc(sb + AUG_A + wg * 2048, 128, 256, 0), mk_desc(sb + AUG_B, 128, 256, 0), 1);
      wg_commit();
      const float hr0 = 0.5f * lds64f(sb + SSTAT + (wg * 64 + 16 * w + b0) * 8).y;
      const float hr1 = 0.5f * lds64f(sb + SSTAT + (wg * 64 + 16 * w + b0 + 8) * 8).y;
      wg_wait<0>();
      if (lane == 0) mbar_arrive(BAR(B_G1DONE));
      if (tid == 0) TL(42);
      mbar_wait(BAR(B_G1DONE), 0);
      uint32_t hs = sb + HST + wg * 3 * 8192 + (16 * w + (mi & 1) * 8 + li) * 128 + (((mi >> 1) ^ li) << 4);
#pragma unroll GELU_UNROLL
      for (int ch = 0; ch < 3; ch++) {
        uint32_t o[16];
#pragma unroll
        for (int g = 0; g < 8; g++) {
          const float* a = acc + (GELU_UNROLL == 3 ? 32 * ch : 0) + 4 * g;
          o[2 * g] = gelu2(a[0], a[1], hr0);
          o[2 * g + 1] = gelu2(a[2], a[3], hr1);
        }
#pragma unroll
        for (int p = 0; p < 4; p++) stsm4(hs ^ (p << 5), o[4 * p], o[4 * p + 1], o[4 * p + 2], o[4 * p + 3]);
#pragma unroll
        for (int i = 0; i < (GELU_UNROLL == 3 ? 0 : 64); i++) asm volatile("mov.b32 %0, %1;\n" : "=f"(acc[i]) : "f"(acc[i + 32]));
        fence_async_smem();
        __syncwarp();
        if (lane == 0) mbar_arrive(BAR(B_HCH + wg * 3 + ch));
        if (tid == 0) TL(43 + ch);
        hs += 8192;
      }
    }
    if (wg == 1) {
      const uint32_t tag = tag_bits(read_epoch());
      const int t = tid & 127;
      const __nv_bfloat16* zp = g_z + (ns * 160 + (t >> 3)) * S_ + rb64 * 64 + (t & 7) * 8;
      uint4 zz[8];
#pragma unroll
      for (int i = 0; i < 8; i++) zz[i].x = ~tag;
#pragma unroll 1
      for (int i = w; i < 40; i += 4) {
        const int ch = i >> 3, blk = i & 7, buf = ch & 1;
        if (i >= 36) {
#pragma unroll
          for (int n = 0; n < 8; n++) zz[n] = ld_pkt(reinterpret_cast<const uint4*>(zp + n * 16 * S_));
        }
        const uint32_t ra = sb + RED + buf * RED_BUF + (32 * blk + lane) * 16;
        mbar_wait(BAR(B_RFULL + 8 * buf + blk), (ch >> 1) & 1);
        if (i >= 36) {
          if ((zz[6].x ^ tag) & 0x00010001u) zz[6] = ld_pkt(reinterpret_cast<const uint4*>(zp + 6 * 16 * S_));
          if ((zz[7].x ^ tag) & 0x00010001u) zz[7] = ld_pkt(reinterpret_cast<const uint4*>(zp + 7 * 16 * S_));
        }
        uint4 p[4];
#pragma unroll
        for (int ww = 0; ww < 4; ww++) p[ww] = lds128(ra + ww * RED_P);
        __syncwarp();
        if (lane == 0) mbar_arrive(BAR(B_REMPTY + buf));
        if (blk == 0) {
#pragma unroll
          for (int ww = 1; ww < 4; ww++) if (lane < 2 * ww) p[ww] = make_uint4(0, 0, 0, 0);
        }
        uint32_t o[4];
#pragma unroll
        for (int e = 0; e < 4; e++) {
          const uint32_t a0 = (&p[0].x)[e], a1 = (&p[1].x)[e], a2 = (&p[2].x)[e], a3 = (&p[3].x)[e];
          o[e] = pack_bf16((bf_lo(a0) + bf_lo(a1)) + (bf_lo(a2) + bf_lo(a3)), (bf_hi(a0) + bf_hi(a1)) + (bf_hi(a2) + bf_hi(a3)));
        }
        st_tagged(g_z + (d0 + 32 * ch) * S_ + (32 * blk + lane) * 8, o[0], o[1], o[2], o[3], tag);
        if (lane == 0 && blk == 7 && (TL_ALL || ch == 4)) TL(22 + 3 * ch);
      }
      if (!ZH_D && lane == 0) flag_arrive_relaxed(FL_ZH + (b >> 5));
      ld_tagged<8, 1, false>(zz, zp, 16 * S_, 0, tag);
      if (t == 96) TL(55);
      mbar_wait(BAR(B_CEMPTY), 0);
#pragma unroll
      for (int n = 0; n < 8; n++)
        sts128(sb + FIN_Z + (t >> 3) * 128 + (((t & 7) ^ ((t >> 3) & 7)) << 4) + n * 2048, zz[n].x, zz[n].y, zz[n].z, zz[n].w);
      __syncwarp();
      if (lane == 0) mbar_arrive(BAR(B_RDONE));
      const BaseCtx k = base_ctx(sb, rb64 & 1, w, lane);
      mbar_wait(BAR(B_FINX), 0);
      mbar_wait(BAR(B_RDONE), 0);
#pragma unroll 1
      for (int q = 0; q < 2; q++) base_block(k, q);
      __syncwarp();
      if (lane == 0) mbar_arrive(BAR(B_BASE));
    } else {
      float acc[80];
      const uint32_t lo0 = (sb & 0x3FFFF) >> 4;
      const uint32_t own = lo0 + ((HST + (rb64 & 1) * 3 * 8192) >> 4), oth = lo0 + ((HST + ((rb64 & 1) ^ 1) * 3 * 8192) >> 4);
#define G2_DESC(lo, lbo) (((uint64_t)0x40000040u << 32) | (uint64_t)((lo) | ((lbo) << 12)))
#define G2_TILE(A, B, S)                                                                                     \
  {                                                                                                          \
    const bool more = (S) > 0 || r > 0;                                                                      \
    if ((S) < 3 && r == 0) mbar_wait(BAR(B_HCH + (S)) + (rb64 & 1) * 24, 0);                                 \
    const int tk = (5 * r + (S) - 3) * G2_TMUL / G2_TDIV + G2_TOFF;                                          \
    const bool gated = 5 * r + (S) >= 3 && (unsigned)tk < 10u;                                                         \
    const bool rdy = !gated && __all_sync(~0u, mbar_try_nb(BAR(B_FULL2 + (S)), r & 1));                      \
    if (!rdy) {                                                                                              \
      wg_wait<0>();                                                                                          \
      if (more && lane == 0) mbar_arrive(BAR(B_EMPTY2 + ((S) + 4) % 5));                                     \
      mbar_wait(BAR(B_FULL2 + (S)), r & 1);                                                                  \
      if (gated) mbar_wait(BAR(B_TOK + tk), 0);                                                              \
    }                                                                                                        \
    wg_fence();                                                                                              \
    _Pragma("unroll") for (int kk = 0; kk < 4; kk++)                                                         \
      wgmma_n160_bmn(acc, G2_DESC((A) + 2 * kk, 16), G2_DESC((B) + 128 * kk, 8192), more || kk != 0);        \
    wg_commit();                                                                                             \
    if (rdy) { wg_wait<1>(); if (more && lane == 0) mbar_arrive(BAR(B_EMPTY2 + ((S) + 4) % 5)); }            \
  }
#define G2_B(S) (lz + ((R2B + (((S) + 1) & 3) * ST2B_BYTES) >> 4))
#pragma unroll 1
      for (int r = 0;; r++) {
        uint32_t z;
        asm volatile("mov.u32 %0, 0;\n" : "=r"(z));
        z = __shfl_sync(~0u, z, 0);
        const uint32_t lz = lo0 + z, a3 = (r == 0 ? own : oth) + z;
        if (tid == 0) TL(80 + 5 * r);
        G2_TILE(a3, G2_B(0), 0) G2_TILE(a3 + 512, G2_B(1), 1) G2_TILE(a3 + 1024, G2_B(2), 2)
        G2_TILE(lz + (R2A >> 4), G2_B(3), 3)
        if (r == 4) break;
        G2_TILE(lz + ((R2A + 8192) >> 4), own + z, 4)
      }
      if (tid == 0) TL(103);
#define TBLK(p) ((p) < 8 ? ((p) >> 1) + rot : (rot ? 0 : 4))
      uint32_t base[40];
      const int xr = (mi & 1) * 8 + li;
      const uint32_t xa0 = sb + FIN_X + w * 5120 + xr * 64 + (((mi >> 1) ^ ((xr >> 1) & 3)) << 4);
      mbar_wait(BAR(B_BASE), 0);
#pragma unroll
      for (int p = 0; p < 10; p++) ldsm4((xa0 ^ ((p & 1) << 5)) + TBLK(p) * 1024, base + 4 * p);
      wg_wait<0>();
      if (tid == 0) TL(49);
#pragma unroll
      for (int p = 0; p < 10; p++) {
        uint32_t o[4];
#pragma unroll
        for (int e = 0; e < 4; e++) o[e] = bfma2(pack_bf16(acc[8 * p + 2 * e], acc[8 * p + 2 * e + 1]), ONE2, base[4 * p + e]);
        stsm4((xa0 ^ ((p & 1) << 5)) + TBLK(p) * 1024, o[0], o[1], o[2], o[3]);
      }
      fence_async_smem();
      __syncwarp();
      if (elect_one()) {
        tma3d_store(&P.out, 0, rb64 * 64 + w * 16, ns * 5, sb + FIN_X + w * 5120);
        bulk_commit();
        if (w == 0) flag_arrive_relaxed(FL_DONE);
        bulk_wait_read<0>();
        if (w == 0) TL(50);
      }
    }
  }
}

typedef CUresult (*EncodeFn)(CUtensorMap*, CUtensorMapDataType, cuuint32_t, void*, const cuuint64_t*, const cuuint64_t*,
                             const cuuint32_t*, const cuuint32_t*, CUtensorMapInterleave, CUtensorMapSwizzle,
                             CUtensorMapL2promotion, CUtensorMapFloatOOBfill);

void enc2d(EncodeFn f, CUtensorMap* m, const void* p, uint64_t d0, uint64_t d1, uint32_t b0, uint32_t b1, CUtensorMapSwizzle sw) {
  cuuint64_t dims[2] = {d0, d1}, str[1] = {d0 * 2};
  cuuint32_t box[2] = {b0, b1}, es[2] = {1, 1};
  f(m, CU_TENSOR_MAP_DATA_TYPE_BFLOAT16, 2, const_cast<void*>(p), dims, str, box, es, CU_TENSOR_MAP_INTERLEAVE_NONE, sw,
    CU_TENSOR_MAP_L2_PROMOTION_L2_128B, CU_TENSOR_MAP_FLOAT_OOB_FILL_NONE);
}
void enc3d(EncodeFn f, CUtensorMap* m, const void* p, uint64_t rows, uint64_t cols, uint32_t blk, uint32_t brows, uint32_t bblk,
           CUtensorMapSwizzle sw) {
  cuuint64_t dims[3] = {blk, rows, cols / blk}, str[2] = {cols * 2, (uint64_t)blk * 2};
  cuuint32_t box[3] = {blk, brows, bblk}, es[3] = {1, 1, 1};
  f(m, CU_TENSOR_MAP_DATA_TYPE_BFLOAT16, 3, const_cast<void*>(p), dims, str, box, es, CU_TENSOR_MAP_INTERLEAVE_NONE, sw,
    CU_TENSOR_MAP_L2_PROMOTION_L2_128B, CU_TENSOR_MAP_FLOAT_OOB_FILL_NONE);
}

}

extern "C" void kernel_launch(void* const* d_in, const int* in_sizes, int n_in, void* d_out, int out_size) {
  (void)in_sizes; (void)n_in; (void)out_size;
  static EncodeFn enc = nullptr;
  static void *ph = nullptr, *pu = nullptr;
  if (!enc) {
    void* fn = nullptr;
    cudaDriverEntryPointQueryResult qr;
    cudaGetDriverEntryPoint("cuTensorMapEncodeTiled", &fn, cudaEnableDefault, &qr);
    enc = (EncodeFn)fn;
    cudaGetSymbolAddress(&ph, g_h);
    cudaGetSymbolAddress(&pu, g_u);
    cudaFuncSetAttribute(fused_kernel, cudaFuncAttributeMaxDynamicSharedMemorySize, SMEM_ALLOC);
  }
  typedef const __nv_bfloat16* bp;
  Params P;
  P.x = (bp)d_in[0]; P.k = (bp)d_in[1]; P.v = (bp)d_in[2]; P.shift_k = (bp)d_in[3]; P.ssm_k = (bp)d_in[4]; P.ssm_D = (bp)d_in[5];
  P.w1p = (bp)d_in[7]; P.b1 = (bp)d_in[8]; P.w2p = (bp)d_in[9]; P.b2 = (bp)d_in[10];
  enc2d(enc, &P.x_a, P.x, D_, S_, 64, 128, CU_TENSOR_MAP_SWIZZLE_128B);
  enc3d(enc, &P.w1, P.w1p, D_, F_, 64, 64, 3, CU_TENSOR_MAP_SWIZZLE_128B);
  enc3d(enc, &P.kt, P.k, S_, D_, 64, 35, 1, CU_TENSOR_MAP_SWIZZLE_NONE);
  enc3d(enc, &P.vt, P.v, S_, D_, 64, 32, 1, CU_TENSOR_MAP_SWIZZLE_NONE);
  {
    cuuint64_t dims[4] = {S_, 4, 8, 20}, str[3] = {8 * S_ * 2, S_ * 2, 32 * S_ * 2};
    cuuint32_t box[4] = {32, 4, 8, 1}, es[4] = {1, 1, 1, 1};
    enc(&P.ut, CU_TENSOR_MAP_DATA_TYPE_BFLOAT16, 4, pu, dims, str, box, es, CU_TENSOR_MAP_INTERLEAVE_NONE, CU_TENSOR_MAP_SWIZZLE_64B,
        CU_TENSOR_MAP_L2_PROMOTION_NONE, CU_TENSOR_MAP_FLOAT_OOB_FILL_NONE);
  }
  enc2d(enc, &P.h, ph, F_, S_, 64, 64, CU_TENSOR_MAP_SWIZZLE_128B);
  enc3d(enc, &P.w2, P.w2p, F_, D_, 64, 64, 2, CU_TENSOR_MAP_SWIZZLE_128B);
  enc3d(enc, &P.w23, P.w2p, F_, D_, 64, 64, 3, CU_TENSOR_MAP_SWIZZLE_128B);
  enc2d(enc, &P.w2h, P.w2p, D_, F_, 32, 64, CU_TENSOR_MAP_SWIZZLE_128B);
  enc3d(enc, &P.x_t, P.x, S_, D_, 32, 16, 5, CU_TENSOR_MAP_SWIZZLE_64B);
  enc3d(enc, &P.out, d_out, S_, D_, 32, 16, 5, CU_TENSOR_MAP_SWIZZLE_64B);
  fused_kernel<<<NCTA, 512, SMEM_ALLOC, cudaStreamPerThread>>>(P);
}
```
